```python
import torch

def _softmax(x, axis=-1):
    return torch.softmax(x, dim=axis)
def _gelu(x):
    return torch.nn.functional.gelu(x, approximate="tanh")
def _silu(x):
    return torch.nn.functional.silu(x)
def _sigmoid(x):
    return torch.sigmoid(x)
def _layernorm(x, axis=-1, eps=1e-5):
    m = x.mean(dim=axis, keepdim=True)
    v = x.var(dim=axis, keepdim=True, unbiased=False)
    return (x - m) / torch.sqrt(v + eps)
def _scatter_add(tgt, idx, src, axis=0):
    return tgt.clone().index_add_(axis, idx, src)
def _segment_sum(src, seg, n):
    out = torch.zeros((n,) + src.shape[1:], dtype=src.dtype)
    return out.index_add_(0, seg, src)
def _pad(x, pw):
    flat = tuple(v for pair in reversed(pw) for v in pair)
    return torch.nn.functional.pad(x, flat)

kernel_name = 'recurrent_scan__sliding_block_cached__glu_gated_bilinear__prompt'

def setup_inputs():

    _w = (lambda a: (lambda t: t.to(torch.bfloat16) if t.is_floating_point() else t)(torch.as_tensor(a)))
    def _A_setup():
        B, Sq, D = 1, 2048, 640
        Hq, Hkv, Sk, Dh = 32, 32, 2048, 192
        assert Hq % Hkv == 0, (Hq, Hkv)
        return {
            "x": _w((lambda *s: torch.randn(*s, dtype=torch.bfloat16) * 0.05)(B, Sq, D)),
            "k_cache": _w((lambda *s: torch.randn(*s, dtype=torch.bfloat16) * 1.6)(B, Hkv, Sk, Dh)),
            "v_cache": _w((lambda *s: torch.randn(*s, dtype=torch.bfloat16) * 1.6)(B, Hkv, Sk, Dh)),
            "wq": _w((lambda *s: torch.randn(*s, dtype=torch.bfloat16) * 1.6)(D, Hq * Dh) * (D ** -0.5)),
            "wo": _w((lambda *s: torch.randn(*s, dtype=torch.bfloat16) * 1.6)(Hq * Dh, D) * ((Hq * Dh) ** -0.5)),
        }
    _A_in = _A_setup()

    def _B_setup():
        B, S, D, F = 1, 2048, 640, 1536
        return {
            "x": _w((lambda *s: torch.randn(*s, dtype=torch.bfloat16) * 0.05)(B, S, D)),
            "w_gate": _w((lambda *s: torch.randn(*s, dtype=torch.bfloat16) * 0.2)(D, F) * (D ** -0.5)),
            "w_up": _w((lambda *s: torch.randn(*s, dtype=torch.bfloat16) * 0.2)(D, F) * (D ** -0.5)),
            "w_down": _w((lambda *s: torch.randn(*s, dtype=torch.bfloat16) * 0.2)(F, D) * (F ** -0.5)),
        }
    _B_in = _B_setup()

    return {
        "A_x": _A_in["x"],
        "A_k_cache": _A_in["k_cache"],
        "A_v_cache": _A_in["v_cache"],
        "A_wq": _A_in["wq"],
        "A_wo": _A_in["wo"],
        "B_x": _B_in["x"],
        "B_w_gate": _B_in["w_gate"],
        "B_w_up": _B_in["w_up"],
        "B_w_down": _B_in["w_down"],
    }

def reference(A_x, A_k_cache, A_v_cache, A_wq, A_wo, B_x, B_w_gate, B_w_up, B_w_down):
    def _A_ref(x, k_cache, v_cache, wq, wo):
        B, Sq, D = x.shape
        Hq, Dh = 32, 192
        Hkv, Sk = k_cache.shape[1], k_cache.shape[2]
        W = min(4096, max(256, Sk // 4))
        rep = Hq // Hkv
        q = (lambda x, *d: x.permute(*d))((x @ wq).reshape(B, Sq, Hq, Dh), 0, 2, 1, 3)
        k = (lambda x, n, axis: torch.repeat_interleave(x, n, dim=axis))(k_cache[:, :, Sk - W:, :], rep, axis=1)
        v = (lambda x, n, axis: torch.repeat_interleave(x, n, dim=axis))(v_cache[:, :, Sk - W:, :], rep, axis=1)
        scores = torch.einsum("bhqd,bhkd->bhqk", q, k) * (Dh ** -0.5)
        p = _softmax(scores, axis=-1)
        o = torch.einsum("bhqk,bhkd->bhqd", p, v)
        return (lambda x, *d: x.permute(*d))(o, 0, 2, 1, 3).reshape(B, Sq, Hq * Dh) @ wo

    def _B_ref(x, w_gate, w_up, w_down):
        g = torch.einsum("bsd,df->bsf", x, w_gate)
        u = torch.einsum("bsd,df->bsf", x, w_up)
        h = g * u
        return torch.einsum("bsf,fd->bsd", h, w_down)

    x = A_x
    xn = _layernorm(x, axis=-1)
    s = _A_ref(xn, A_k_cache, A_v_cache, A_wq, A_wo)
    g = _silu(_B_ref(xn, B_w_gate, B_w_up, B_w_down))
    return x + s * g
```

```cpp
#include <cuda_runtime.h>
#include <cuda_bf16.h>
#include <cuda.h>
#include <stdint.h>

namespace {

__device__ __forceinline__ void wgmma_ss_n192_t1(float (&d)[96], uint64_t descA, uint64_t descB, int scaleD) {
  asm volatile("{\n.reg .pred p;\nsetp.ne.b32 p, %98, 0;\n"
      "wgmma.mma_async.sync.aligned.m64n192k16.f32.bf16.bf16 {"
      "%0, %1, %2, %3, %4, %5, %6, %7, %8, %9, %10, %11, %12, %13, %14, %15,"
      "%16, %17, %18, %19, %20, %21, %22, %23, %24, %25, %26, %27, %28, %29, %30, %31,"
      "%32, %33, %34, %35, %36, %37, %38, %39, %40, %41, %42, %43, %44, %45, %46, %47,"
      "%48, %49, %50, %51, %52, %53, %54, %55, %56, %57, %58, %59, %60, %61, %62, %63,"
      "%64, %65, %66, %67, %68, %69, %70, %71, %72, %73, %74, %75, %76, %77, %78, %79,"
      "%80, %81, %82, %83, %84, %85, %86, %87, %88, %89, %90, %91, %92, %93, %94, %95},"
      "%96, %97, p, 1, 1, 0, 1;\n}\n"
      : "+f"(d[0]), "+f"(d[1]), "+f"(d[2]), "+f"(d[3]), "+f"(d[4]), "+f"(d[5]), "+f"(d[6]), "+f"(d[7]),
        "+f"(d[8]), "+f"(d[9]), "+f"(d[10]), "+f"(d[11]), "+f"(d[12]), "+f"(d[13]), "+f"(d[14]), "+f"(d[15]),
        "+f"(d[16]), "+f"(d[17]), "+f"(d[18]), "+f"(d[19]), "+f"(d[20]), "+f"(d[21]), "+f"(d[22]), "+f"(d[23]),
        "+f"(d[24]), "+f"(d[25]), "+f"(d[26]), "+f"(d[27]), "+f"(d[28]), "+f"(d[29]), "+f"(d[30]), "+f"(d[31]),
        "+f"(d[32]), "+f"(d[33]), "+f"(d[34]), "+f"(d[35]), "+f"(d[36]), "+f"(d[37]), "+f"(d[38]), "+f"(d[39]),
        "+f"(d[40]), "+f"(d[41]), "+f"(d[42]), "+f"(d[43]), "+f"(d[44]), "+f"(d[45]), "+f"(d[46]), "+f"(d[47]),
        "+f"(d[48]), "+f"(d[49]), "+f"(d[50]), "+f"(d[51]), "+f"(d[52]), "+f"(d[53]), "+f"(d[54]), "+f"(d[55]),
        "+f"(d[56]), "+f"(d[57]), "+f"(d[58]), "+f"(d[59]), "+f"(d[60]), "+f"(d[61]), "+f"(d[62]), "+f"(d[63]),
        "+f"(d[64]), "+f"(d[65]), "+f"(d[66]), "+f"(d[67]), "+f"(d[68]), "+f"(d[69]), "+f"(d[70]), "+f"(d[71]),
        "+f"(d[72]), "+f"(d[73]), "+f"(d[74]), "+f"(d[75]), "+f"(d[76]), "+f"(d[77]), "+f"(d[78]), "+f"(d[79]),
        "+f"(d[80]), "+f"(d[81]), "+f"(d[82]), "+f"(d[83]), "+f"(d[84]), "+f"(d[85]), "+f"(d[86]), "+f"(d[87]),
        "+f"(d[88]), "+f"(d[89]), "+f"(d[90]), "+f"(d[91]), "+f"(d[92]), "+f"(d[93]), "+f"(d[94]), "+f"(d[95])
      : "l"(descA), "l"(descB), "r"(scaleD));
}
__device__ __forceinline__ void wgmma_rs_n64_t0(float (&d)[32], uint32_t a0, uint32_t a1, uint32_t a2, uint32_t a3, uint64_t descB, int scaleD) {
  asm volatile("{\n.reg .pred p;\nsetp.ne.b32 p, %37, 0;\n"
      "wgmma.mma_async.sync.aligned.m64n64k16.f32.bf16.bf16 {"
      "%0, %1, %2, %3, %4, %5, %6, %7, %8, %9, %10, %11, %12, %13, %14, %15,"
      "%16, %17, %18, %19, %20, %21, %22, %23, %24, %25, %26, %27, %28, %29, %30, %31},"
      "{%32, %33, %34, %35}, %36, p, 1, 1, 0;\n}\n"
      : "+f"(d[0]), "+f"(d[1]), "+f"(d[2]), "+f"(d[3]), "+f"(d[4]), "+f"(d[5]), "+f"(d[6]), "+f"(d[7]),
        "+f"(d[8]), "+f"(d[9]), "+f"(d[10]), "+f"(d[11]), "+f"(d[12]), "+f"(d[13]), "+f"(d[14]), "+f"(d[15]),
        "+f"(d[16]), "+f"(d[17]), "+f"(d[18]), "+f"(d[19]), "+f"(d[20]), "+f"(d[21]), "+f"(d[22]), "+f"(d[23]),
        "+f"(d[24]), "+f"(d[25]), "+f"(d[26]), "+f"(d[27]), "+f"(d[28]), "+f"(d[29]), "+f"(d[30]), "+f"(d[31])
      : "r"(a0), "r"(a1), "r"(a2), "r"(a3), "l"(descB), "r"(scaleD));
}
__device__ __forceinline__ void wgmma_rs_n192_t1(float (&d)[96], uint32_t a0, uint32_t a1, uint32_t a2, uint32_t a3, uint64_t descB, int scaleD) {
  asm volatile("{\n.reg .pred p;\nsetp.ne.b32 p, %101, 0;\n"
      "wgmma.mma_async.sync.aligned.m64n192k16.f32.bf16.bf16 {"
      "%0, %1, %2, %3, %4, %5, %6, %7, %8, %9, %10, %11, %12, %13, %14, %15,"
      "%16, %17, %18, %19, %20, %21, %22, %23, %24, %25, %26, %27, %28, %29, %30, %31,"
      "%32, %33, %34, %35, %36, %37, %38, %39, %40, %41, %42, %43, %44, %45, %46, %47,"
      "%48, %49, %50, %51, %52, %53, %54, %55, %56, %57, %58, %59, %60, %61, %62, %63,"
      "%64, %65, %66, %67, %68, %69, %70, %71, %72, %73, %74, %75, %76, %77, %78, %79,"
      "%80, %81, %82, %83, %84, %85, %86, %87, %88, %89, %90, %91, %92, %93, %94, %95},"
      "{%96, %97, %98, %99}, %100, p, 1, 1, 1;\n}\n"
      : "+f"(d[0]), "+f"(d[1]), "+f"(d[2]), "+f"(d[3]), "+f"(d[4]), "+f"(d[5]), "+f"(d[6]), "+f"(d[7]),
        "+f"(d[8]), "+f"(d[9]), "+f"(d[10]), "+f"(d[11]), "+f"(d[12]), "+f"(d[13]), "+f"(d[14]), "+f"(d[15]),
        "+f"(d[16]), "+f"(d[17]), "+f"(d[18]), "+f"(d[19]), "+f"(d[20]), "+f"(d[21]), "+f"(d[22]), "+f"(d[23]),
        "+f"(d[24]), "+f"(d[25]), "+f"(d[26]), "+f"(d[27]), "+f"(d[28]), "+f"(d[29]), "+f"(d[30]), "+f"(d[31]),
        "+f"(d[32]), "+f"(d[33]), "+f"(d[34]), "+f"(d[35]), "+f"(d[36]), "+f"(d[37]), "+f"(d[38]), "+f"(d[39]),
        "+f"(d[40]), "+f"(d[41]), "+f"(d[42]), "+f"(d[43]), "+f"(d[44]), "+f"(d[45]), "+f"(d[46]), "+f"(d[47]),
        "+f"(d[48]), "+f"(d[49]), "+f"(d[50]), "+f"(d[51]), "+f"(d[52]), "+f"(d[53]), "+f"(d[54]), "+f"(d[55]),
        "+f"(d[56]), "+f"(d[57]), "+f"(d[58]), "+f"(d[59]), "+f"(d[60]), "+f"(d[61]), "+f"(d[62]), "+f"(d[63]),
        "+f"(d[64]), "+f"(d[65]), "+f"(d[66]), "+f"(d[67]), "+f"(d[68]), "+f"(d[69]), "+f"(d[70]), "+f"(d[71]),
        "+f"(d[72]), "+f"(d[73]), "+f"(d[74]), "+f"(d[75]), "+f"(d[76]), "+f"(d[77]), "+f"(d[78]), "+f"(d[79]),
        "+f"(d[80]), "+f"(d[81]), "+f"(d[82]), "+f"(d[83]), "+f"(d[84]), "+f"(d[85]), "+f"(d[86]), "+f"(d[87]),
        "+f"(d[88]), "+f"(d[89]), "+f"(d[90]), "+f"(d[91]), "+f"(d[92]), "+f"(d[93]), "+f"(d[94]), "+f"(d[95])
      : "r"(a0), "r"(a1), "r"(a2), "r"(a3), "l"(descB), "r"(scaleD));
}
__device__ __forceinline__ void wgmma_ss_n160_t1(float (&d)[80], uint64_t descA, uint64_t descB, int scaleD) {
  asm volatile("{\n.reg .pred p;\nsetp.ne.b32 p, %82, 0;\n"
      "wgmma.mma_async.sync.aligned.m64n160k16.f32.bf16.bf16 {"
      "%0, %1, %2, %3, %4, %5, %6, %7, %8, %9, %10, %11, %12, %13, %14, %15,"
      "%16, %17, %18, %19, %20, %21, %22, %23, %24, %25, %26, %27, %28, %29, %30, %31,"
      "%32, %33, %34, %35, %36, %37, %38, %39, %40, %41, %42, %43, %44, %45, %46, %47,"
      "%48, %49, %50, %51, %52, %53, %54, %55, %56, %57, %58, %59, %60, %61, %62, %63,"
      "%64, %65, %66, %67, %68, %69, %70, %71, %72, %73, %74, %75, %76, %77, %78, %79},"
      "%80, %81, p, 1, 1, 0, 1;\n}\n"
      : "+f"(d[0]), "+f"(d[1]), "+f"(d[2]), "+f"(d[3]), "+f"(d[4]), "+f"(d[5]), "+f"(d[6]), "+f"(d[7]),
        "+f"(d[8]), "+f"(d[9]), "+f"(d[10]), "+f"(d[11]), "+f"(d[12]), "+f"(d[13]), "+f"(d[14]), "+f"(d[15]),
        "+f"(d[16]), "+f"(d[17]), "+f"(d[18]), "+f"(d[19]), "+f"(d[20]), "+f"(d[21]), "+f"(d[22]), "+f"(d[23]),
        "+f"(d[24]), "+f"(d[25]), "+f"(d[26]), "+f"(d[27]), "+f"(d[28]), "+f"(d[29]), "+f"(d[30]), "+f"(d[31]),
        "+f"(d[32]), "+f"(d[33]), "+f"(d[34]), "+f"(d[35]), "+f"(d[36]), "+f"(d[37]), "+f"(d[38]), "+f"(d[39]),
        "+f"(d[40]), "+f"(d[41]), "+f"(d[42]), "+f"(d[43]), "+f"(d[44]), "+f"(d[45]), "+f"(d[46]), "+f"(d[47]),
        "+f"(d[48]), "+f"(d[49]), "+f"(d[50]), "+f"(d[51]), "+f"(d[52]), "+f"(d[53]), "+f"(d[54]), "+f"(d[55]),
        "+f"(d[56]), "+f"(d[57]), "+f"(d[58]), "+f"(d[59]), "+f"(d[60]), "+f"(d[61]), "+f"(d[62]), "+f"(d[63]),
        "+f"(d[64]), "+f"(d[65]), "+f"(d[66]), "+f"(d[67]), "+f"(d[68]), "+f"(d[69]), "+f"(d[70]), "+f"(d[71]),
        "+f"(d[72]), "+f"(d[73]), "+f"(d[74]), "+f"(d[75]), "+f"(d[76]), "+f"(d[77]), "+f"(d[78]), "+f"(d[79])
      : "l"(descA), "l"(descB), "r"(scaleD));
}

constexpr int SEQ = 2048, DM = 640, NH = 32, DH = 192, SKV = 2048, WIN = 512, FF = 1536;
constexpr int KOH = NH * DH + FF;
constexpr int NW = 6, NX = 5;
constexpr int WSLOT = 24576, XSLOT = 16384;
constexpr int LO_STEPS = 58;
constexpr int SMEM_BYTES = NW * WSLOT + NX * XSLOT + 1024 + 256;
constexpr unsigned ITEM_TARGET = 64;
constexpr int SPIN_LIMIT = 1 << 24;

__device__ __nv_bfloat16 g_xn[SEQ * DM];
__device__ __nv_bfloat16 g_oh[SEQ * KOH];
__device__ float4 g_part[64 * 20 * 256];
__device__ unsigned g_cnt[16 * 32];
__device__ unsigned g_flag_part[64 * 8];

struct Params {
  CUtensorMap xn, wq, wg, wu, k, v, oh, wo, wd, x, out;
};

__device__ __forceinline__ uint32_t smem_u32(const void* p) { return (uint32_t)__cvta_generic_to_shared(p); }
__device__ __forceinline__ void mbar_init(uint32_t bar, uint32_t cnt) {
  asm volatile("mbarrier.init.shared::cta.b64 [%0], %1;" ::"r"(bar), "r"(cnt) : "memory");
}
__device__ __forceinline__ void mbar_expect_tx(uint32_t bar, uint32_t bytes) {
  asm volatile("mbarrier.arrive.expect_tx.shared::cta.b64 _, [%0], %1;" ::"r"(bar), "r"(bytes) : "memory");
}
__device__ __forceinline__ void mbar_wait(uint32_t bar, uint32_t parity) {
  asm volatile(
      "{\n.reg .pred p;\n.reg .u32 c;\n"
      "mbarrier.try_wait.parity.shared::cta.b64 p, [%0], %1;\n"
      "@p bra.uni DONE;\n"
      "mov.u32 c, 0;\n"
      "LOOP:\n"
      "mbarrier.try_wait.parity.shared::cta.b64 p, [%0], %1;\n"
      "@p bra.uni DONE;\n"
      "add.u32 c, c, 1;\n"
      "setp.lt.u32 p, c, 4194304;\n"
      "@p bra.uni LOOP;\n"
      "trap;\n"
      "DONE:\n}" ::"r"(bar), "r"(parity) : "memory");
}
__device__ __forceinline__ void mbar_arrive_cluster(uint32_t addr) {
  asm volatile("mbarrier.arrive.shared::cluster.b64 _, [%0];" ::"r"(addr) : "memory");
}
__device__ __forceinline__ void mbar_arrive(uint32_t addr) {
  asm volatile("mbarrier.arrive.shared::cta.b64 _, [%0];" ::"r"(addr) : "memory");
}
__device__ __forceinline__ bool elect_one() {
  uint32_t p;
  asm volatile("{\n.reg .pred q;\nelect.sync _|q, 0xffffffff;\nselp.u32 %0, 1, 0, q;\n}" : "=r"(p));
  return p;
}
__device__ __forceinline__ void tma2d(uint32_t dst, const CUtensorMap* m, int c0, int c1, uint32_t bar) {
  asm volatile("cp.async.bulk.tensor.2d.shared::cluster.global.mbarrier::complete_tx::bytes [%0], [%1, {%3, %4}], [%2];"
               ::"r"(dst), "l"(m), "r"(bar), "r"(c0), "r"(c1) : "memory");
}
__device__ __forceinline__ void tma3d(uint32_t dst, const CUtensorMap* m, int c0, int c1, int c2, uint32_t bar) {
  asm volatile("cp.async.bulk.tensor.3d.shared::cluster.global.mbarrier::complete_tx::bytes [%0], [%1, {%3, %4, %5}], [%2];"
               ::"r"(dst), "l"(m), "r"(bar), "r"(c0), "r"(c1), "r"(c2) : "memory");
}
__device__ __forceinline__ void tma4d_mc(uint32_t dst, const CUtensorMap* m, int c2, int c3, uint32_t bar) {
  asm volatile("cp.async.bulk.tensor.4d.shared::cluster.global.mbarrier::complete_tx::bytes.multicast::cluster"
               " [%0], [%1, {%3, %3, %4, %5}], [%2], %6;"
               ::"r"(dst), "l"(m), "r"(bar), "r"(0), "r"(c2), "r"(c3), "h"((uint16_t)3) : "memory");
}
__device__ __forceinline__ void tma5d_mc(uint32_t dst, const CUtensorMap* m, int c2, int c3, uint32_t bar) {
  asm volatile("cp.async.bulk.tensor.5d.shared::cluster.global.mbarrier::complete_tx::bytes.multicast::cluster"
               " [%0], [%1, {%3, %3, %4, %5, %3}], [%2], %6;"
               ::"r"(dst), "l"(m), "r"(bar), "r"(0), "r"(c2), "r"(c3), "h"((uint16_t)3) : "memory");
}
__device__ __forceinline__ void tma3d_store(const CUtensorMap* m, uint32_t src, int c0, int c1, int c2) {
  asm volatile("cp.async.bulk.tensor.3d.global.shared::cta.bulk_group [%0, {%2, %3, %4}], [%1];"
               ::"l"(m), "r"(src), "r"(c0), "r"(c1), "r"(c2) : "memory");
}
__device__ __forceinline__ void wgmma_fence() { asm volatile("wgmma.fence.sync.aligned;" ::: "memory"); }
__device__ __forceinline__ void wgmma_commit() { asm volatile("wgmma.commit_group.sync.aligned;" ::: "memory"); }
template <int N> __device__ __forceinline__ void wgmma_wait() {
  asm volatile("wgmma.wait_group.sync.aligned %0;" ::"n"(N) : "memory");
}
template <int N> __device__ __forceinline__ void pin(float (&a)[N]) {
#pragma unroll
  for (int i = 0; i < N; i++) asm volatile("" : "+f"(a[i])::"memory");
}
template <int N> __device__ __forceinline__ void pin(uint32_t (&a)[N]) {
#pragma unroll
  for (int i = 0; i < N; i++) asm volatile("" : "+r"(a[i])::"memory");
}
__device__ __forceinline__ uint64_t mk_desc(uint32_t lo, uint32_t hi) {
  uint64_t d;
  asm("mov.b64 %0, {%1, %2};" : "=l"(d) : "r"(lo), "r"(hi));
  return d;
}
__device__ __forceinline__ uint32_t pack_bf16(float lo, float hi) {
  uint32_t r;
  asm("cvt.rn.bf16x2.f32 %0, %1, %2;" : "=r"(r) : "f"(hi), "f"(lo));
  return r;
}
__device__ __forceinline__ uint32_t mul_bf16x2(uint32_t a, uint32_t b) {
  uint32_t r;
  asm("mul.rn.bf16x2 %0, %1, %2;" : "=r"(r) : "r"(a), "r"(b));
  return r;
}
__device__ __forceinline__ uint32_t add_bf16x2(uint32_t a, uint32_t b) {
  uint32_t r;
  asm("add.rn.bf16x2 %0, %1, %2;" : "=r"(r) : "r"(a), "r"(b));
  return r;
}
__device__ __forceinline__ float ex2(float x) {
  float r;
  asm("ex2.approx.ftz.f32 %0, %1;" : "=f"(r) : "f"(x));
  return r;
}
__device__ __forceinline__ float bf_lo(uint32_t v) { return __uint_as_float(v << 16); }
__device__ __forceinline__ float bf_hi(uint32_t v) { return __uint_as_float(v & 0xffff0000u); }
__device__ __forceinline__ void wait_counter(const unsigned* p, unsigned target) {
  for (int i = 0;; i++) {
    unsigned v;
    asm volatile("ld.acquire.gpu.global.u32 %0, [%1];" : "=r"(v) : "l"(p) : "memory");
    if (v >= target) break;
    if (i > SPIN_LIMIT) __trap();
    __nanosleep(20);
  }
}
__device__ __forceinline__ void signal_counter(unsigned* p, int lane) {
  asm volatile("fence.proxy.async.global;" ::: "memory");
  __threadfence();
  __syncwarp();
  if (lane == 0) asm volatile("red.relaxed.gpu.global.add.u32 [%0], 1;" ::"l"(p) : "memory");
}

constexpr uint32_t DESC_HI_A = (1024 >> 4) | (1u << 30);
constexpr uint32_t DESC_HI_B = (3072 >> 4) | (1u << 30);
constexpr uint32_t DESC_HI_F = (2560 >> 4) | (2u << 30);
constexpr uint32_t LBO_B = (1024 >> 4) << 16;
constexpr uint32_t LBO_F = (512 >> 4) << 16;

struct Cons {
  uint32_t wbase, xbase;
  uint32_t fullW, fullX, emptyX, emptyW_rem;
  uint32_t ws, wph, xs, xph;
  int lane, wg;
  __device__ __forceinline__ void waitW() { mbar_wait(fullW + ws * 8, wph); }
  __device__ __forceinline__ void waitX() { mbar_wait(fullX + xs * 8, xph); }
  __device__ __forceinline__ uint32_t advW() { uint32_t s = ws; if (++ws == NW) { ws = 0; wph ^= 1; } return s; }
  __device__ __forceinline__ uint32_t advX() { uint32_t s = xs; if (++xs == NX) { xs = 0; xph ^= 1; } return s; }
  __device__ __forceinline__ void relW(uint32_t s) { if (lane < 2) mbar_arrive_cluster(emptyW_rem + s * 8); }
  __device__ __forceinline__ void relX(uint32_t s) { if (lane == 0) mbar_arrive(emptyX + s * 8); }
  __device__ __forceinline__ void turn_begin() { asm volatile("bar.sync %0, 256;" ::"r"(1 + wg) : "memory"); }
  __device__ __forceinline__ void turn_end() { asm volatile("bar.arrive %0, 256;" ::"r"(2 - wg) : "memory"); }
};

__device__ __forceinline__ void proj_gemm(Cons& c, float (&acc)[96], unsigned* pending_signal) {
#pragma unroll 1
  for (int ks = 0; ks < 10; ks++) {
    c.waitX();
    c.waitW();
    uint32_t a = c.xbase + c.xs * (XSLOT >> 4);
    uint32_t b = (c.wbase + c.ws * (WSLOT >> 4)) | LBO_B;
    c.turn_begin();
    pin(acc);
    wgmma_fence();
#pragma unroll
    for (int kk = 0; kk < 4; kk++)
      wgmma_ss_n192_t1(acc, mk_desc(a + kk * 2, DESC_HI_A), mk_desc(b + kk * (6144 >> 4), DESC_HI_B), (kk > 0) | (ks > 0));
    wgmma_commit();
    c.turn_end();
    uint32_t sx = c.advX(), sw = c.advW();
    if (ks == 2 && pending_signal != nullptr) signal_counter(pending_signal, c.lane);
    wgmma_wait<0>();
    pin(acc);
    c.relX(sx);
    c.relW(sw);
  }
}

__device__ __forceinline__ void issue_qk(Cons& c, float (&s)[32], uint32_t (&qf)[48], uint32_t slot) {
  uint32_t b = c.wbase + slot * (WSLOT >> 4);
#pragma unroll
  for (int kk = 0; kk < 12; kk++)
    wgmma_rs_n64_t0(s, qf[4 * kk], qf[4 * kk + 1], qf[4 * kk + 2], qf[4 * kk + 3],
                    mk_desc(b + (kk >> 2) * (1024 >> 4) + (kk & 3) * 2, DESC_HI_B), kk > 0);
}
__device__ __forceinline__ void issue_pv(Cons& c, float (&acc)[96], uint32_t (&pf)[16], uint32_t slot, int accum) {
  uint32_t b = (c.wbase + slot * (WSLOT >> 4)) | LBO_B;
#pragma unroll
  for (int kk = 0; kk < 4; kk++)
    wgmma_rs_n192_t1(acc, pf[4 * kk], pf[4 * kk + 1], pf[4 * kk + 2], pf[4 * kk + 3],
                     mk_desc(b + kk * (6144 >> 4), DESC_HI_B), (kk > 0) | accum);
}

constexpr float SM_SCALE = 0.07216878364870322f * 1.4426950408889634f;

__device__ __forceinline__ void softmax_block(float (&s)[32], float& m0, float& m1, float& l0, float& l1,
                                              float& a0, float& a1) {
  float x0 = fmaxf(s[0], s[1]), x1 = fmaxf(s[2], s[3]);
#pragma unroll
  for (int j = 1; j < 8; j++) {
    x0 = fmaxf(x0, fmaxf(s[4 * j], s[4 * j + 1]));
    x1 = fmaxf(x1, fmaxf(s[4 * j + 2], s[4 * j + 3]));
  }
  x0 = fmaxf(x0, __shfl_xor_sync(~0u, x0, 1));
  x1 = fmaxf(x1, __shfl_xor_sync(~0u, x1, 1));
  x0 = fmaxf(x0, __shfl_xor_sync(~0u, x0, 2));
  x1 = fmaxf(x1, __shfl_xor_sync(~0u, x1, 2));
  x0 = fmaxf(x0, m0);
  x1 = fmaxf(x1, m1);
  a0 = ex2((m0 - x0) * SM_SCALE);
  a1 = ex2((m1 - x1) * SM_SCALE);
  m0 = x0;
  m1 = x1;
  float c0 = -x0 * SM_SCALE, c1 = -x1 * SM_SCALE;
  float t0 = 0.f, t1 = 0.f;
#pragma unroll
  for (int j = 0; j < 8; j++) {
    s[4 * j] = ex2(fmaf(s[4 * j], SM_SCALE, c0));
    s[4 * j + 1] = ex2(fmaf(s[4 * j + 1], SM_SCALE, c0));
    s[4 * j + 2] = ex2(fmaf(s[4 * j + 2], SM_SCALE, c1));
    s[4 * j + 3] = ex2(fmaf(s[4 * j + 3], SM_SCALE, c1));
    t0 += s[4 * j] + s[4 * j + 1];
    t1 += s[4 * j + 2] + s[4 * j + 3];
  }
  l0 = fmaf(l0, a0, t0);
  l1 = fmaf(l1, a1, t1);
}

__device__ __forceinline__ void store_oh(const uint32_t (&p)[48], __nv_bfloat16* dst) {
#pragma unroll
  for (int g = 0; g < 6; g++) {
    *reinterpret_cast<uint4*>(dst + 32 * g) = make_uint4(p[8 * g], p[8 * g + 2], p[8 * g + 4], p[8 * g + 6]);
    *reinterpret_cast<uint4*>(dst + 32 * g + 8 * KOH) = make_uint4(p[8 * g + 1], p[8 * g + 3], p[8 * g + 5], p[8 * g + 7]);
  }
}

__device__ __forceinline__ void final_gemm(Cons& c, float (&acc)[80], int nsteps, unsigned* pending_signal) {
#pragma unroll 1
  for (int ks = 0; ks < nsteps; ks++) {
    c.waitX();
    c.waitW();
    uint32_t a = c.xbase + c.xs * (XSLOT >> 4);
    uint32_t b = (c.wbase + c.ws * (WSLOT >> 4)) | LBO_F;
    c.turn_begin();
    pin(acc);
    wgmma_fence();
#pragma unroll
    for (int kk = 0; kk < 4; kk++)
      wgmma_ss_n160_t1(acc, mk_desc(a + kk * 2, DESC_HI_A), mk_desc(b + kk * (5120 >> 4), DESC_HI_F), (kk > 0) | (ks > 0));
    wgmma_commit();
    c.turn_end();
    uint32_t sx = c.advX(), sw = c.advW();
    if (ks == 2 && pending_signal != nullptr) signal_counter(pending_signal, c.lane);
    wgmma_wait<0>();
    pin(acc);
    c.relX(sx);
    c.relW(sw);
  }
}

__global__ void __cluster_dims__(2, 1, 1) __launch_bounds__(384, 1)
fused_kernel(const __grid_constant__ Params P, const __nv_bfloat16* __restrict__ x) {
  extern __shared__ uint8_t smem_raw[];
  const uint32_t s0 = smem_u32(smem_raw);
  const uint32_t wring = (s0 + 256 + 1023) & ~1023u;
  const uint32_t xring = wring + NW * WSLOT;
  const uint32_t fullW = s0, emptyW = s0 + 64, fullX = s0 + 128, emptyX = s0 + 192;
  const int tid = threadIdx.x;
  const int warp = __shfl_sync(~0u, tid >> 5, 0);
  const int lane = tid & 31;
  const int rank = blockIdx.x & 1;
  const int cl = blockIdx.x >> 1;
  const int slot = cl & 7;
  const int qt = (cl >> 3) * 2 + rank;
  unsigned* cnt = g_cnt + qt * 32;
  const int hi = slot >> 2, nc = slot & 3;

  uint2 xv[2][5];
  const int lnrow = qt * 128 + slot * 16 + warp * 2;
  if (warp < 8) {
#pragma unroll
    for (int r = 0; r < 2; r++)
#pragma unroll
      for (int i = 0; i < 5; i++)
        xv[r][i] = __ldg(reinterpret_cast<const uint2*>(x + (size_t)(lnrow + r) * DM + i * 128 + lane * 4));
  }
  if (tid == 256) {
    for (int i = 0; i < NW; i++) { mbar_init(fullW + i * 8, 1); mbar_init(emptyW + i * 8, 16); }
    for (int i = 0; i < NX; i++) { mbar_init(fullX + i * 8, 1); mbar_init(emptyX + i * 8, 8); }
    asm volatile("fence.mbarrier_init.release.cluster;" ::: "memory");
  }
  __syncwarp();
  asm volatile("barrier.cluster.arrive.relaxed.aligned;" ::: "memory");
  if (warp < 8) {
#pragma unroll
    for (int r = 0; r < 2; r++) {
      float v[20];
#pragma unroll
      for (int i = 0; i < 5; i++) {
        v[4 * i] = bf_lo(xv[r][i].x); v[4 * i + 1] = bf_hi(xv[r][i].x);
        v[4 * i + 2] = bf_lo(xv[r][i].y); v[4 * i + 3] = bf_hi(xv[r][i].y);
      }
      float sum = 0.f;
#pragma unroll
      for (int i = 0; i < 20; i++) sum += v[i];
#pragma unroll
      for (int o = 16; o > 0; o >>= 1) sum += __shfl_xor_sync(~0u, sum, o);
      const float mean = sum * (1.0f / DM);
      float sq = 0.f;
#pragma unroll
      for (int i = 0; i < 20; i++) { v[i] -= mean; sq = fmaf(v[i], v[i], sq); }
#pragma unroll
      for (int o = 16; o > 0; o >>= 1) sq += __shfl_xor_sync(~0u, sq, o);
      const float rstd = rsqrtf(sq * (1.0f / DM) + 1e-5f);
#pragma unroll
      for (int i = 0; i < 5; i++)
        *reinterpret_cast<uint2*>(g_xn + (size_t)(lnrow + r) * DM + i * 128 + lane * 4) =
            make_uint2(pack_bf16(v[4 * i] * rstd, v[4 * i + 1] * rstd), pack_bf16(v[4 * i + 2] * rstd, v[4 * i + 3] * rstd));
    }
    signal_counter(cnt + 0, lane);
  }
  asm volatile("barrier.cluster.wait.aligned;" ::: "memory");

  if (warp >= 8) {
    asm volatile("setmaxnreg.dec.sync.aligned.u32 40;");
    if (warp == 8) {
      uint32_t s = 0, ph = 1;
      const uint32_t dst = wring + rank * 12288;
      auto load4 = [&](const CUtensorMap* m, int c2, int c3) {
        mbar_wait(emptyW + s * 8, ph);
        if (elect_one()) {
          mbar_expect_tx(fullW + s * 8, WSLOT);
          tma4d_mc(dst + s * WSLOT, m, c2, c3 + rank * 4, fullW + s * 8);
        }
        __syncwarp();
        if (++s == NW) { s = 0; ph ^= 1; }
      };
      auto load5 = [&](const CUtensorMap* m, int ks) {
        mbar_wait(emptyW + s * 8, ph);
        if (elect_one()) {
          mbar_expect_tx(fullW + s * 8, 20480);
          tma5d_mc(wring + rank * 10240 + s * WSLOT, m, ks * 8 + rank * 4, nc * 5, fullW + s * 8);
        }
        __syncwarp();
        if (++s == NW) { s = 0; ph ^= 1; }
      };
#pragma unroll 1
      for (int ks = 0; ks < 10; ks++) load4(&P.wg, slot * 3, ks * 8);
#pragma unroll 1
      for (int ks = 0; ks < 10; ks++) load4(&P.wu, slot * 3, ks * 8);
#pragma unroll 1
      for (int it = 0; it < 4; it++) {
        const int h = it * 8 + slot;
#pragma unroll 1
        for (int ks = 0; ks < 10; ks++) load4(&P.wq, h * 3, ks * 8);
        const int g0 = (h * SKV + (SKV - WIN)) / 8;
        load4(&P.k, 0, g0);
#pragma unroll 1
        for (int j = 0; j < 7; j++) {
          load4(&P.k, 0, g0 + (j + 1) * 8);
          load4(&P.v, 0, g0 + j * 8);
        }
        load4(&P.v, 0, g0 + 56);
      }
      if (hi) {
#pragma unroll 1
        for (int ks = 0; ks < 24; ks++) load5(&P.wd, ks);
#pragma unroll 1
        for (int ks = LO_STEPS; ks < 96; ks++) load5(&P.wo, ks);
#pragma unroll 1
        for (int w = 0; w < 2; w++) {
          mbar_wait(emptyW + s * 8, ph);
          if (elect_one()) {
            mbar_expect_tx(fullW + s * 8, 20480);
            tma3d(wring + s * WSLOT, &P.x, 0, qt * 128 + w * 64, nc * 5, fullW + s * 8);
          }
          __syncwarp();
          if (++s == NW) { s = 0; ph ^= 1; }
        }
      } else {
#pragma unroll 1
        for (int ks = 0; ks < LO_STEPS; ks++) load5(&P.wo, ks);
      }
    } else if (warp == 9) {
      uint32_t s = 0, ph = 1;
      auto load2 = [&](const CUtensorMap* m, int col) {
        mbar_wait(emptyX + s * 8, ph);
        if (elect_one()) {
          mbar_expect_tx(fullX + s * 8, XSLOT);
          tma2d(xring + s * XSLOT, m, col, qt * 128, fullX + s * 8);
        }
        __syncwarp();
        if (++s == NX) { s = 0; ph ^= 1; }
      };
      wait_counter(cnt + 0, ITEM_TARGET);
      asm volatile("fence.proxy.async.global;" ::: "memory");
#pragma unroll 1
      for (int p = 0; p < 6; p++)
#pragma unroll 1
        for (int ks = 0; ks < 10; ks++) load2(&P.xn, ks * 64);
      int ks0 = 0, ks1 = LO_STEPS;
      if (hi) {
        wait_counter(cnt + 1, ITEM_TARGET);
        asm volatile("fence.proxy.async.global;" ::: "memory");
#pragma unroll 1
        for (int ks = 0; ks < 24; ks++) load2(&P.oh, NH * DH + ks * 64);
        ks0 = LO_STEPS; ks1 = 96;
      }
#pragma unroll 1
      for (int ks = ks0; ks < ks1; ks++) {
        if (ks == ks0 || ks % 24 == 0) {
          wait_counter(cnt + 2 + ks / 24, ITEM_TARGET);
          asm volatile("fence.proxy.async.global;" ::: "memory");
        }
        load2(&P.oh, ks * 64);
      }
      if (lane == 0) {
        __threadfence();
        unsigned old = atomicAdd(cnt + 6, 1);
        if (old == 7) {
          __threadfence();
#pragma unroll
          for (int i = 0; i < 7; i++) cnt[i] = 0;
        }
      }
      __syncwarp();
    }
  } else {
    asm volatile("setmaxnreg.inc.sync.aligned.u32 232;");
    Cons c;
    c.lane = lane;
    c.wg = warp >> 2;
    c.wbase = (wring & 0x3FFFF) >> 4;
    c.xbase = (((xring + c.wg * 8192) & 0x3FFFF) >> 4) | (1u << 16);
    c.fullW = fullW; c.fullX = fullX; c.emptyX = emptyX;
    asm volatile("mapa.shared::cluster.u32 %0, %1, %2;" : "=r"(c.emptyW_rem) : "r"(emptyW), "r"(lane & 1));
    c.ws = c.wph = c.xs = c.xph = 0;
    if (c.wg == 1) asm volatile("bar.arrive 1, 256;" ::: "memory");
    const int row = qt * 128 + warp * 16 + (lane >> 2);
    __nv_bfloat16* ohrow = g_oh + (size_t)row * KOH + (lane & 3) * 8;

    {
      float acc[96];
      uint32_t qf[48];
      proj_gemm(c, acc, nullptr);
#pragma unroll
      for (int i = 0; i < 48; i++) qf[i] = pack_bf16(acc[2 * i], acc[2 * i + 1]);
      proj_gemm(c, acc, nullptr);
#pragma unroll
      for (int i = 0; i < 48; i++) qf[i] = mul_bf16x2(qf[i], pack_bf16(acc[2 * i], acc[2 * i + 1]));
      store_oh(qf, ohrow + NH * DH + slot * DH);

#pragma unroll 1
      for (int it = 0; it < 4; it++) {
        proj_gemm(c, acc, cnt + 1 + it);
#pragma unroll
        for (int i = 0; i < 48; i++) qf[i] = pack_bf16(acc[2 * i], acc[2 * i + 1]);
        float s[32];
        uint32_t pf[16];
        float m0 = -INFINITY, m1 = -INFINITY, l0 = 0.f, l1 = 0.f, a0, a1;
        {
          c.waitW();
          uint32_t sk = c.advW();
          c.turn_begin();
          pin(qf);
          wgmma_fence();
          issue_qk(c, s, qf, sk);
          wgmma_commit();
          c.turn_end();
          wgmma_wait<0>();
          pin(s);
          c.relW(sk);
          softmax_block(s, m0, m1, l0, l1, a0, a1);
#pragma unroll
          for (int i = 0; i < 16; i++) pf[i] = pack_bf16(s[2 * i], s[2 * i + 1]);
        }
#pragma unroll 1
        for (int j = 0; j < 7; j++) {
          c.waitW();
          uint32_t sk = c.advW();
          c.waitW();
          uint32_t sv = c.advW();
          c.turn_begin();
          pin(s); pin(pf); pin(acc);
          wgmma_fence();
          issue_qk(c, s, qf, sk);
          wgmma_commit();
          issue_pv(c, acc, pf, sv, j > 0);
          wgmma_commit();
          c.turn_end();
          wgmma_wait<1>();
          pin(s);
          c.relW(sk);
          softmax_block(s, m0, m1, l0, l1, a0, a1);
          wgmma_wait<0>();
          pin(acc); pin(pf);
          c.relW(sv);
#pragma unroll
          for (int i = 0; i < 24; i++) {
            acc[4 * i] *= a0; acc[4 * i + 1] *= a0;
            acc[4 * i + 2] *= a1; acc[4 * i + 3] *= a1;
          }
#pragma unroll
          for (int i = 0; i < 16; i++) pf[i] = pack_bf16(s[2 * i], s[2 * i + 1]);
        }
        {
          c.waitW();
          uint32_t sv = c.advW();
          c.turn_begin();
          pin(pf); pin(acc);
          wgmma_fence();
          issue_pv(c, acc, pf, sv, 1);
          wgmma_commit();
          c.turn_end();
          l0 += __shfl_xor_sync(~0u, l0, 1);
          l1 += __shfl_xor_sync(~0u, l1, 1);
          l0 += __shfl_xor_sync(~0u, l0, 2);
          l1 += __shfl_xor_sync(~0u, l1, 2);
          const float r0 = 1.0f / l0, r1 = 1.0f / l1;
          wgmma_wait<0>();
          pin(acc); pin(pf);
          c.relW(sv);
#pragma unroll
          for (int i = 0; i < 24; i++) {
            qf[2 * i] = pack_bf16(acc[4 * i] * r0, acc[4 * i + 1] * r0);
            qf[2 * i + 1] = pack_bf16(acc[4 * i + 2] * r1, acc[4 * i + 3] * r1);
          }
          store_oh(qf, ohrow + (it * 8 + slot) * DH);
        }
      }
    }

    {
      float acc[80];
      const int tile = qt * 4 + nc;
      float4* part = g_part + (size_t)tile * 20 * 256 + tid;
      unsigned* flag = g_flag_part + tile * 8 + warp;
      if (!hi) {
        final_gemm(c, acc, LO_STEPS, cnt + 5);
#pragma unroll
        for (int i = 0; i < 20; i++)
          __stcg(part + i * 256, make_float4(acc[4 * i], acc[4 * i + 1], acc[4 * i + 2], acc[4 * i + 3]));
        __threadfence();
        __syncwarp();
        if (lane == 0) asm volatile("st.relaxed.gpu.global.u32 [%0], %1;" ::"l"(flag), "r"(1u) : "memory");
      } else {
        uint32_t gate[40];
        final_gemm(c, acc, 24, cnt + 5);
#pragma unroll
        for (int i = 0; i < 40; i++) {
          uint32_t d = pack_bf16(acc[2 * i], acc[2 * i + 1]);
          float d0 = bf_lo(d), d1 = bf_hi(d);
          float g0 = __fdividef(d0, 1.0f + ex2(-1.4426950408889634f * d0));
          float g1 = __fdividef(d1, 1.0f + ex2(-1.4426950408889634f * d1));
          gate[i] = pack_bf16(g0, g1);
        }
        final_gemm(c, acc, 96 - LO_STEPS, nullptr);
        wait_counter(flag, 1);
        __syncwarp();
        if (lane == 0) asm volatile("st.relaxed.gpu.global.u32 [%0], %1;" ::"l"(flag), "r"(0u) : "memory");
#pragma unroll
        for (int i = 0; i < 20; i++) {
          float4 p = __ldcg(part + i * 256);
          acc[4 * i] += p.x; acc[4 * i + 1] += p.y; acc[4 * i + 2] += p.z; acc[4 * i + 3] += p.w;
        }
        if (c.wg == 1) c.advW();
        c.waitW();
        const uint32_t xt = wring + c.ws * WSLOT;
        const int r = (warp & 3) * 16 + (lane & 7) + ((lane >> 3) & 1) * 8;
        const uint32_t rb = xt + r * 64;
        const uint32_t sw = (r >> 1) & 3;
#pragma unroll
        for (int i = 0; i < 10; i++) {
          const uint32_t addr = rb + (i >> 1) * 4096 + ((((i & 1) * 2 + (lane >> 4)) ^ sw) << 4);
          uint32_t x0, x1, x2, x3;
          asm volatile("ldmatrix.sync.aligned.m8n8.x4.shared.b16 {%0, %1, %2, %3}, [%4];"
                       : "=r"(x0), "=r"(x1), "=r"(x2), "=r"(x3) : "r"(addr) : "memory");
          x0 = add_bf16x2(x0, mul_bf16x2(pack_bf16(acc[8 * i], acc[8 * i + 1]), gate[4 * i]));
          x1 = add_bf16x2(x1, mul_bf16x2(pack_bf16(acc[8 * i + 2], acc[8 * i + 3]), gate[4 * i + 1]));
          x2 = add_bf16x2(x2, mul_bf16x2(pack_bf16(acc[8 * i + 4], acc[8 * i + 5]), gate[4 * i + 2]));
          x3 = add_bf16x2(x3, mul_bf16x2(pack_bf16(acc[8 * i + 6], acc[8 * i + 7]), gate[4 * i + 3]));
          asm volatile("stmatrix.sync.aligned.m8n8.x4.shared.b16 [%4], {%0, %1, %2, %3};"
                       ::"r"(x0), "r"(x1), "r"(x2), "r"(x3), "r"(addr) : "memory");
        }
        asm volatile("fence.proxy.async.shared::cta;" ::: "memory");
        asm volatile("bar.sync %0, 128;" ::"r"(3 + c.wg) : "memory");
        if ((warp & 3) == 0 && elect_one()) {
          tma3d_store(&P.out, xt, 0, qt * 128 + c.wg * 64, nc * 5);
          asm volatile("cp.async.bulk.commit_group;" ::: "memory");
          asm volatile("cp.async.bulk.wait_group 0;" ::: "memory");
        }
        __syncwarp();
      }
    }
  }
  asm volatile("barrier.cluster.arrive.aligned;" ::: "memory");
  asm volatile("barrier.cluster.wait.aligned;" ::: "memory");
}

typedef CUresult (*EncodeFn)(CUtensorMap*, CUtensorMapDataType, cuuint32_t, void*, const cuuint64_t*, const cuuint64_t*,
                             const cuuint32_t*, const cuuint32_t*, CUtensorMapInterleave, CUtensorMapSwizzle,
                             CUtensorMapL2promotion, CUtensorMapFloatOOBfill);

void make_map(EncodeFn enc, CUtensorMap* m, const void* ptr, int rank, const cuuint64_t* dims, const cuuint64_t* strides,
              const cuuint32_t* box, CUtensorMapSwizzle sw) {
  cuuint32_t es[5] = {1, 1, 1, 1, 1};
  enc(m, CU_TENSOR_MAP_DATA_TYPE_BFLOAT16, rank, const_cast<void*>(ptr), dims, strides, box, es,
      CU_TENSOR_MAP_INTERLEAVE_NONE, sw, CU_TENSOR_MAP_L2_PROMOTION_L2_128B, CU_TENSOR_MAP_FLOAT_OOB_FILL_NONE);
}

void map_b192(EncodeFn enc, CUtensorMap* m, const void* ptr, uint64_t rows, uint64_t cols) {
  cuuint64_t d[4] = {64, 8, cols / 64, rows / 8};
  cuuint64_t s[3] = {cols * 2, 128, cols * 2 * 8};
  cuuint32_t b[4] = {64, 8, 3, 4};
  make_map(enc, m, ptr, 4, d, s, b, CU_TENSOR_MAP_SWIZZLE_128B);
}
void map_b160(EncodeFn enc, CUtensorMap* m, const void* ptr, uint64_t rows) {
  const uint64_t p = DM * 2;
  cuuint64_t d[5] = {32, 2, rows / 8, DM / 32, 4};
  cuuint64_t s[4] = {p, 8 * p, 64, 2 * p};
  cuuint32_t b[5] = {32, 2, 4, 5, 4};
  make_map(enc, m, ptr, 5, d, s, b, CU_TENSOR_MAP_SWIZZLE_64B);
}
void map_a(EncodeFn enc, CUtensorMap* m, const void* ptr, uint64_t cols) {
  cuuint64_t d[2] = {cols, SEQ};
  cuuint64_t s[1] = {cols * 2};
  cuuint32_t b[2] = {64, 128};
  make_map(enc, m, ptr, 2, d, s, b, CU_TENSOR_MAP_SWIZZLE_128B);
}
void map_xo(EncodeFn enc, CUtensorMap* m, const void* ptr) {
  cuuint64_t d[3] = {32, SEQ, DM / 32};
  cuuint64_t s[2] = {DM * 2, 64};
  cuuint32_t b[3] = {32, 64, 5};
  make_map(enc, m, ptr, 3, d, s, b, CU_TENSOR_MAP_SWIZZLE_64B);
}

}

extern "C" void kernel_launch(void* const* d_in, const int* in_sizes, int n_in, void* d_out, int out_size) {
  void* fn = nullptr;
  cudaDriverEntryPointQueryResult qr;
  cudaGetDriverEntryPoint("cuTensorMapEncodeTiled", &fn, cudaEnableDefault, &qr);
  EncodeFn enc = (EncodeFn)fn;
  void *xn, *oh;
  cudaGetSymbolAddress(&xn, g_xn);
  cudaGetSymbolAddress(&oh, g_oh);
  Params P;
  map_a(enc, &P.xn, xn, DM);
  map_a(enc, &P.oh, oh, KOH);
  map_b192(enc, &P.wq, d_in[3], DM, NH * DH);
  map_b192(enc, &P.wg, d_in[6], DM, FF);
  map_b192(enc, &P.wu, d_in[7], DM, FF);
  map_b192(enc, &P.k, d_in[1], (uint64_t)NH * SKV, DH);
  map_b192(enc, &P.v, d_in[2], (uint64_t)NH * SKV, DH);
  map_b160(enc, &P.wo, d_in[4], NH * DH);
  map_b160(enc, &P.wd, d_in[8], FF);
  map_xo(enc, &P.x, d_in[0]);
  map_xo(enc, &P.out, d_out);
  cudaFuncSetAttribute(fused_kernel, cudaFuncAttributeMaxDynamicSharedMemorySize, SMEM_BYTES);
  fused_kernel<<<128, 384, SMEM_BYTES>>>(P, (const __nv_bfloat16*)d_in[0]);
}
```

```cpp
#include <cuda_runtime.h>
#include <cuda_bf16.h>
#include <cuda.h>
#include <stddef.h>
#include <stdint.h>

namespace {

__device__ __forceinline__ void wgmma_ss_n192_t1(float (&d)[96], uint64_t descA, uint64_t descB, int scaleD) {
  asm volatile("{\n.reg .pred p;\nsetp.ne.b32 p, %98, 0;\n"
      "wgmma.mma_async.sync.aligned.m64n192k16.f32.bf16.bf16 {"
      "%0, %1, %2, %3, %4, %5, %6, %7, %8, %9, %10, %11, %12, %13, %14, %15,"
      "%16, %17, %18, %19, %20, %21, %22, %23, %24, %25, %26, %27, %28, %29, %30, %31,"
      "%32, %33, %34, %35, %36, %37, %38, %39, %40, %41, %42, %43, %44, %45, %46, %47,"
      "%48, %49, %50, %51, %52, %53, %54, %55, %56, %57, %58, %59, %60, %61, %62, %63,"
      "%64, %65, %66, %67, %68, %69, %70, %71, %72, %73, %74, %75, %76, %77, %78, %79,"
      "%80, %81, %82, %83, %84, %85, %86, %87, %88, %89, %90, %91, %92, %93, %94, %95},"
      "%96, %97, p, 1, 1, 0, 1;\n}\n"
      : "+f"(d[0]), "+f"(d[1]), "+f"(d[2]), "+f"(d[3]), "+f"(d[4]), "+f"(d[5]), "+f"(d[6]), "+f"(d[7]),
        "+f"(d[8]), "+f"(d[9]), "+f"(d[10]), "+f"(d[11]), "+f"(d[12]), "+f"(d[13]), "+f"(d[14]), "+f"(d[15]),
        "+f"(d[16]), "+f"(d[17]), "+f"(d[18]), "+f"(d[19]), "+f"(d[20]), "+f"(d[21]), "+f"(d[22]), "+f"(d[23]),
        "+f"(d[24]), "+f"(d[25]), "+f"(d[26]), "+f"(d[27]), "+f"(d[28]), "+f"(d[29]), "+f"(d[30]), "+f"(d[31]),
        "+f"(d[32]), "+f"(d[33]), "+f"(d[34]), "+f"(d[35]), "+f"(d[36]), "+f"(d[37]), "+f"(d[38]), "+f"(d[39]),
        "+f"(d[40]), "+f"(d[41]), "+f"(d[42]), "+f"(d[43]), "+f"(d[44]), "+f"(d[45]), "+f"(d[46]), "+f"(d[47]),
        "+f"(d[48]), "+f"(d[49]), "+f"(d[50]), "+f"(d[51]), "+f"(d[52]), "+f"(d[53]), "+f"(d[54]), "+f"(d[55]),
        "+f"(d[56]), "+f"(d[57]), "+f"(d[58]), "+f"(d[59]), "+f"(d[60]), "+f"(d[61]), "+f"(d[62]), "+f"(d[63]),
        "+f"(d[64]), "+f"(d[65]), "+f"(d[66]), "+f"(d[67]), "+f"(d[68]), "+f"(d[69]), "+f"(d[70]), "+f"(d[71]),
        "+f"(d[72]), "+f"(d[73]), "+f"(d[74]), "+f"(d[75]), "+f"(d[76]), "+f"(d[77]), "+f"(d[78]), "+f"(d[79]),
        "+f"(d[80]), "+f"(d[81]), "+f"(d[82]), "+f"(d[83]), "+f"(d[84]), "+f"(d[85]), "+f"(d[86]), "+f"(d[87]),
        "+f"(d[88]), "+f"(d[89]), "+f"(d[90]), "+f"(d[91]), "+f"(d[92]), "+f"(d[93]), "+f"(d[94]), "+f"(d[95])
      : "l"(descA), "l"(descB), "r"(scaleD));
}
__device__ __forceinline__ void wgmma_rs_n64_t0(float (&d)[32], uint32_t a0, uint32_t a1, uint32_t a2, uint32_t a3, uint64_t descB, int scaleD) {
  asm volatile("{\n.reg .pred p;\nsetp.ne.b32 p, %37, 0;\n"
      "wgmma.mma_async.sync.aligned.m64n64k16.f32.bf16.bf16 {"
      "%0, %1, %2, %3, %4, %5, %6, %7, %8, %9, %10, %11, %12, %13, %14, %15,"
      "%16, %17, %18, %19, %20, %21, %22, %23, %24, %25, %26, %27, %28, %29, %30, %31},"
      "{%32, %33, %34, %35}, %36, p, 1, 1, 0;\n}\n"
      : "+f"(d[0]), "+f"(d[1]), "+f"(d[2]), "+f"(d[3]), "+f"(d[4]), "+f"(d[5]), "+f"(d[6]), "+f"(d[7]),
        "+f"(d[8]), "+f"(d[9]), "+f"(d[10]), "+f"(d[11]), "+f"(d[12]), "+f"(d[13]), "+f"(d[14]), "+f"(d[15]),
        "+f"(d[16]), "+f"(d[17]), "+f"(d[18]), "+f"(d[19]), "+f"(d[20]), "+f"(d[21]), "+f"(d[22]), "+f"(d[23]),
        "+f"(d[24]), "+f"(d[25]), "+f"(d[26]), "+f"(d[27]), "+f"(d[28]), "+f"(d[29]), "+f"(d[30]), "+f"(d[31])
      : "r"(a0), "r"(a1), "r"(a2), "r"(a3), "l"(descB), "r"(scaleD));
}
__device__ __forceinline__ void wgmma_rs_n192_t1(float (&d)[96], uint32_t a0, uint32_t a1, uint32_t a2, uint32_t a3, uint64_t descB, int scaleD) {
  asm volatile("{\n.reg .pred p;\nsetp.ne.b32 p, %101, 0;\n"
      "wgmma.mma_async.sync.aligned.m64n192k16.f32.bf16.bf16 {"
      "%0, %1, %2, %3, %4, %5, %6, %7, %8, %9, %10, %11, %12, %13, %14, %15,"
      "%16, %17, %18, %19, %20, %21, %22, %23, %24, %25, %26, %27, %28, %29, %30, %31,"
      "%32, %33, %34, %35, %36, %37, %38, %39, %40, %41, %42, %43, %44, %45, %46, %47,"
      "%48, %49, %50, %51, %52, %53, %54, %55, %56, %57, %58, %59, %60, %61, %62, %63,"
      "%64, %65, %66, %67, %68, %69, %70, %71, %72, %73, %74, %75, %76, %77, %78, %79,"
      "%80, %81, %82, %83, %84, %85, %86, %87, %88, %89, %90, %91, %92, %93, %94, %95},"
      "{%96, %97, %98, %99}, %100, p, 1, 1, 1;\n}\n"
      : "+f"(d[0]), "+f"(d[1]), "+f"(d[2]), "+f"(d[3]), "+f"(d[4]), "+f"(d[5]), "+f"(d[6]), "+f"(d[7]),
        "+f"(d[8]), "+f"(d[9]), "+f"(d[10]), "+f"(d[11]), "+f"(d[12]), "+f"(d[13]), "+f"(d[14]), "+f"(d[15]),
        "+f"(d[16]), "+f"(d[17]), "+f"(d[18]), "+f"(d[19]), "+f"(d[20]), "+f"(d[21]), "+f"(d[22]), "+f"(d[23]),
        "+f"(d[24]), "+f"(d[25]), "+f"(d[26]), "+f"(d[27]), "+f"(d[28]), "+f"(d[29]), "+f"(d[30]), "+f"(d[31]),
        "+f"(d[32]), "+f"(d[33]), "+f"(d[34]), "+f"(d[35]), "+f"(d[36]), "+f"(d[37]), "+f"(d[38]), "+f"(d[39]),
        "+f"(d[40]), "+f"(d[41]), "+f"(d[42]), "+f"(d[43]), "+f"(d[44]), "+f"(d[45]), "+f"(d[46]), "+f"(d[47]),
        "+f"(d[48]), "+f"(d[49]), "+f"(d[50]), "+f"(d[51]), "+f"(d[52]), "+f"(d[53]), "+f"(d[54]), "+f"(d[55]),
        "+f"(d[56]), "+f"(d[57]), "+f"(d[58]), "+f"(d[59]), "+f"(d[60]), "+f"(d[61]), "+f"(d[62]), "+f"(d[63]),
        "+f"(d[64]), "+f"(d[65]), "+f"(d[66]), "+f"(d[67]), "+f"(d[68]), "+f"(d[69]), "+f"(d[70]), "+f"(d[71]),
        "+f"(d[72]), "+f"(d[73]), "+f"(d[74]), "+f"(d[75]), "+f"(d[76]), "+f"(d[77]), "+f"(d[78]), "+f"(d[79]),
        "+f"(d[80]), "+f"(d[81]), "+f"(d[82]), "+f"(d[83]), "+f"(d[84]), "+f"(d[85]), "+f"(d[86]), "+f"(d[87]),
        "+f"(d[88]), "+f"(d[89]), "+f"(d[90]), "+f"(d[91]), "+f"(d[92]), "+f"(d[93]), "+f"(d[94]), "+f"(d[95])
      : "r"(a0), "r"(a1), "r"(a2), "r"(a3), "l"(descB), "r"(scaleD));
}
__device__ __forceinline__ void wgmma_ss_n160_t1(float (&d)[80], uint64_t descA, uint64_t descB, int scaleD) {
  asm volatile("{\n.reg .pred p;\nsetp.ne.b32 p, %82, 0;\n"
      "wgmma.mma_async.sync.aligned.m64n160k16.f32.bf16.bf16 {"
      "%0, %1, %2, %3, %4, %5, %6, %7, %8, %9, %10, %11, %12, %13, %14, %15,"
      "%16, %17, %18, %19, %20, %21, %22, %23, %24, %25, %26, %27, %28, %29, %30, %31,"
      "%32, %33, %34, %35, %36, %37, %38, %39, %40, %41, %42, %43, %44, %45, %46, %47,"
      "%48, %49, %50, %51, %52, %53, %54, %55, %56, %57, %58, %59, %60, %61, %62, %63,"
      "%64, %65, %66, %67, %68, %69, %70, %71, %72, %73, %74, %75, %76, %77, %78, %79},"
      "%80, %81, p, 1, 1, 0, 1;\n}\n"
      : "+f"(d[0]), "+f"(d[1]), "+f"(d[2]), "+f"(d[3]), "+f"(d[4]), "+f"(d[5]), "+f"(d[6]), "+f"(d[7]),
        "+f"(d[8]), "+f"(d[9]), "+f"(d[10]), "+f"(d[11]), "+f"(d[12]), "+f"(d[13]), "+f"(d[14]), "+f"(d[15]),
        "+f"(d[16]), "+f"(d[17]), "+f"(d[18]), "+f"(d[19]), "+f"(d[20]), "+f"(d[21]), "+f"(d[22]), "+f"(d[23]),
        "+f"(d[24]), "+f"(d[25]), "+f"(d[26]), "+f"(d[27]), "+f"(d[28]), "+f"(d[29]), "+f"(d[30]), "+f"(d[31]),
        "+f"(d[32]), "+f"(d[33]), "+f"(d[34]), "+f"(d[35]), "+f"(d[36]), "+f"(d[37]), "+f"(d[38]), "+f"(d[39]),
        "+f"(d[40]), "+f"(d[41]), "+f"(d[42]), "+f"(d[43]), "+f"(d[44]), "+f"(d[45]), "+f"(d[46]), "+f"(d[47]),
        "+f"(d[48]), "+f"(d[49]), "+f"(d[50]), "+f"(d[51]), "+f"(d[52]), "+f"(d[53]), "+f"(d[54]), "+f"(d[55]),
        "+f"(d[56]), "+f"(d[57]), "+f"(d[58]), "+f"(d[59]), "+f"(d[60]), "+f"(d[61]), "+f"(d[62]), "+f"(d[63]),
        "+f"(d[64]), "+f"(d[65]), "+f"(d[66]), "+f"(d[67]), "+f"(d[68]), "+f"(d[69]), "+f"(d[70]), "+f"(d[71]),
        "+f"(d[72]), "+f"(d[73]), "+f"(d[74]), "+f"(d[75]), "+f"(d[76]), "+f"(d[77]), "+f"(d[78]), "+f"(d[79])
      : "l"(descA), "l"(descB), "r"(scaleD));
}
__device__ __forceinline__ void wgmma_ss_n128_t1(float (&d)[64], uint64_t descA, uint64_t descB, int scaleD) {
  asm volatile("{\n.reg .pred p;\nsetp.ne.b32 p, %66, 0;\n"
      "wgmma.mma_async.sync.aligned.m64n128k16.f32.bf16.bf16 {"
      "%0, %1, %2, %3, %4, %5, %6, %7, %8, %9, %10, %11, %12, %13, %14, %15,"
      "%16, %17, %18, %19, %20, %21, %22, %23, %24, %25, %26, %27, %28, %29, %30, %31,"
      "%32, %33, %34, %35, %36, %37, %38, %39, %40, %41, %42, %43, %44, %45, %46, %47,"
      "%48, %49, %50, %51, %52, %53, %54, %55, %56, %57, %58, %59, %60, %61, %62, %63},"
      "%64, %65, p, 1, 1, 0, 1;\n}\n"
      : "+f"(d[0]), "+f"(d[1]), "+f"(d[2]), "+f"(d[3]), "+f"(d[4]), "+f"(d[5]), "+f"(d[6]), "+f"(d[7]),
        "+f"(d[8]), "+f"(d[9]), "+f"(d[10]), "+f"(d[11]), "+f"(d[12]), "+f"(d[13]), "+f"(d[14]), "+f"(d[15]),
        "+f"(d[16]), "+f"(d[17]), "+f"(d[18]), "+f"(d[19]), "+f"(d[20]), "+f"(d[21]), "+f"(d[22]), "+f"(d[23]),
        "+f"(d[24]), "+f"(d[25]), "+f"(d[26]), "+f"(d[27]), "+f"(d[28]), "+f"(d[29]), "+f"(d[30]), "+f"(d[31]),
        "+f"(d[32]), "+f"(d[33]), "+f"(d[34]), "+f"(d[35]), "+f"(d[36]), "+f"(d[37]), "+f"(d[38]), "+f"(d[39]),
        "+f"(d[40]), "+f"(d[41]), "+f"(d[42]), "+f"(d[43]), "+f"(d[44]), "+f"(d[45]), "+f"(d[46]), "+f"(d[47]),
        "+f"(d[48]), "+f"(d[49]), "+f"(d[50]), "+f"(d[51]), "+f"(d[52]), "+f"(d[53]), "+f"(d[54]), "+f"(d[55]),
        "+f"(d[56]), "+f"(d[57]), "+f"(d[58]), "+f"(d[59]), "+f"(d[60]), "+f"(d[61]), "+f"(d[62]), "+f"(d[63])
      : "l"(descA), "l"(descB), "r"(scaleD));
}

constexpr int SEQ = 2048, DM = 640, NH = 32, DH = 192, SKV = 2048, WIN = 512, FF = 1536;
constexpr int KOH = NH * DH + FF;
constexpr int NW = 6, NX = 5;
constexpr int WSLOT = 24576, XSLOT = 16384;
constexpr float SCHED_P = 1400.f;
constexpr float SCHED_R = 56000.f;
constexpr int SMEM_BYTES = NW * WSLOT + NX * XSLOT + 1024 + 256 + 512 + 640;
constexpr unsigned ITEM_TARGET = 64;
constexpr int NEARLY = 2;
constexpr int PAIR_LO = 2;

constexpr int NXE = NW / 2;
constexpr int XP = DM;
struct Scratch {
  unsigned cnt[16 * 32];
  unsigned sched[32 * 16];
  unsigned flag_part[128 * 8];
  unsigned ticket, epoch, pad[254];
  __nv_bfloat16 xn[SEQ * XP];
  uint4 part[64 * 2 * 10 * 128];
  __nv_bfloat16 oh[SEQ * KOH];
};
__device__ __align__(1024) Scratch g_s;
#define g_cnt g_s.cnt
#define g_sched g_s.sched
#define g_flag_part g_s.flag_part
#define g_ticket g_s.ticket
#define g_epoch g_s.epoch
#define g_xn g_s.xn
#define g_part g_s.part
#define g_oh g_s.oh


struct Params {
  CUtensorMap xn, wq, wg, wu, wg2, wu2, k, v, oh, wo, wd, x, out;
};

__device__ __forceinline__ uint32_t smem_u32(const void* p) { return (uint32_t)__cvta_generic_to_shared(p); }
__device__ __forceinline__ void mbar_init(uint32_t bar, uint32_t cnt) {
  asm volatile("mbarrier.init.shared::cta.b64 [%0], %1;" ::"r"(bar), "r"(cnt) : "memory");
}
__device__ __forceinline__ void mbar_wait(uint32_t bar, uint32_t parity) {
  asm volatile(
      "{\n.reg .pred p;\n.reg .u32 c;\n"
      "mbarrier.try_wait.parity.shared::cta.b64 p, [%0], %1;\n"
      "@p bra.uni DONE;\n"
      "mov.u32 c, 0;\n"
      "LOOP:\n"
      "mbarrier.try_wait.parity.shared::cta.b64 p, [%0], %1;\n"
      "@p bra.uni DONE;\n"
      "add.u32 c, c, 1;\n"
      "setp.lt.u32 p, c, 4194304;\n"
      "@p bra.uni LOOP;\n"
      "trap;\n"
      "DONE:\n}" ::"r"(bar), "r"(parity) : "memory");
}
__device__ __forceinline__ void mbar_arrive_cluster(uint32_t addr) {
  asm volatile("mbarrier.arrive.shared::cluster.b64 _, [%0];" ::"r"(addr) : "memory");
}
__device__ __forceinline__ bool elect_one() {
  uint32_t p;
  asm volatile("{\n.reg .pred q;\nelect.sync _|q, 0xffffffff;\nselp.u32 %0, 1, 0, q;\n}" : "=r"(p));
  return p;
}
__device__ __forceinline__ uint64_t policy_evict_first() {
  uint64_t p;
  asm volatile("createpolicy.fractional.L2::evict_first.b64 %0, 1.0;" : "=l"(p));
  return p;
}
__device__ __forceinline__ uint64_t policy_evict_normal() {
  uint64_t p;
  asm volatile("createpolicy.fractional.L2::evict_normal.b64 %0, 1.0;" : "=l"(p));
  return p;
}
#define ELECT "{\n.reg .pred q;\nelect.sync _|q, 0xffffffff;\n@q "
__device__ __forceinline__ void w_expect_tx(uint32_t bar, uint32_t bytes) {
  asm volatile(ELECT "mbarrier.arrive.expect_tx.shared::cta.b64 _, [%0], %1;\n}" ::"r"(bar), "r"(bytes) : "memory");
}
__device__ __forceinline__ void w_tma2d(uint32_t dst, const CUtensorMap* m, int c0, int c1, uint32_t bar, uint64_t pol) {
  asm volatile(ELECT "cp.async.bulk.tensor.2d.shared::cluster.global.mbarrier::complete_tx::bytes.L2::cache_hint"
               " [%0], [%1, {%3, %4}], [%2], %5;\n}" ::"r"(dst), "l"(m), "r"(bar), "r"(c0), "r"(c1), "l"(pol) : "memory");
}
__device__ __forceinline__ void w_tma3d(uint32_t dst, const CUtensorMap* m, int c0, int c1, int c2, uint32_t bar) {
  asm volatile(ELECT "cp.async.bulk.tensor.3d.shared::cluster.global.mbarrier::complete_tx::bytes [%0], [%1, {%3, %4, %5}], [%2];\n}"
               ::"r"(dst), "l"(m), "r"(bar), "r"(c0), "r"(c1), "r"(c2) : "memory");
}
__device__ __forceinline__ void w_tma4d_mc(uint32_t dst, const CUtensorMap* m, int c2, int c3, uint32_t bar, uint64_t pol) {
  asm volatile(ELECT "cp.async.bulk.tensor.4d.shared::cluster.global.mbarrier::complete_tx::bytes.multicast::cluster.L2::cache_hint"
               " [%0], [%1, {%3, %3, %4, %5}], [%2], %6, %7;\n}"
               ::"r"(dst), "l"(m), "r"(bar), "r"(0), "r"(c2), "r"(c3), "h"((uint16_t)3), "l"(pol) : "memory");
}
__device__ __forceinline__ void w_tma5d_mc(uint32_t dst, const CUtensorMap* m, int c2, int c3, uint32_t bar, uint64_t pol) {
  asm volatile(ELECT "cp.async.bulk.tensor.5d.shared::cluster.global.mbarrier::complete_tx::bytes.multicast::cluster.L2::cache_hint"
               " [%0], [%1, {%3, %3, %4, %5, %3}], [%2], %6, %7;\n}"
               ::"r"(dst), "l"(m), "r"(bar), "r"(0), "r"(c2), "r"(c3), "h"((uint16_t)3), "l"(pol) : "memory");
}
__device__ __forceinline__ void w_bulk_load(uint32_t dst, const void* src, uint32_t bytes, uint32_t bar) {
  asm volatile(ELECT "cp.async.bulk.shared::cluster.global.mbarrier::complete_tx::bytes [%0], [%1], %2, [%3];\n}"
               ::"r"(dst), "l"(src), "r"(bytes), "r"(bar) : "memory");
}
__device__ __forceinline__ void bulk_store(void* dst, uint32_t src, uint32_t bytes) {
  asm volatile("cp.async.bulk.global.shared::cta.bulk_group [%0], [%1], %2;" ::"l"(dst), "r"(src), "r"(bytes) : "memory");
}
__device__ __forceinline__ void fence_gpu() { asm volatile("fence.acq_rel.gpu;" ::: "memory"); }
__device__ __forceinline__ void wgmma_fence() { asm volatile("wgmma.fence.sync.aligned;" ::: "memory"); }
__device__ __forceinline__ void wgmma_commit() { asm volatile("wgmma.commit_group.sync.aligned;" ::: "memory"); }
template <int N> __device__ __forceinline__ void wgmma_wait() {
  asm volatile("wgmma.wait_group.sync.aligned %0;" ::"n"(N) : "memory");
}
template <int N> __device__ __forceinline__ void pin(float (&a)[N]) {
#pragma unroll
  for (int i = 0; i < N; i++) asm volatile("" : "+f"(a[i])::"memory");
}
template <int N> __device__ __forceinline__ void pin(uint32_t (&a)[N]) {
#pragma unroll
  for (int i = 0; i < N; i++) asm volatile("" : "+r"(a[i])::"memory");
}
__device__ __forceinline__ uint64_t mk_desc(uint32_t lo, uint32_t hi) {
  uint64_t d;
  asm("mov.b64 %0, {%1, %2};" : "=l"(d) : "r"(lo), "r"(hi));
  return d;
}
__device__ __forceinline__ uint32_t pack_bf16(float lo, float hi) {
  uint32_t r;
  asm("cvt.rn.bf16x2.f32 %0, %1, %2;" : "=r"(r) : "f"(hi), "f"(lo));
  return r;
}
__device__ __forceinline__ uint32_t mul_bf16x2(uint32_t a, uint32_t b) {
  uint32_t r;
  asm("mul.rn.bf16x2 %0, %1, %2;" : "=r"(r) : "r"(a), "r"(b));
  return r;
}
__device__ __forceinline__ uint32_t add_bf16x2(uint32_t a, uint32_t b) {
  uint32_t r;
  asm("add.rn.bf16x2 %0, %1, %2;" : "=r"(r) : "r"(a), "r"(b));
  return r;
}
__device__ __forceinline__ uint32_t fma_bf16x2(uint32_t a, uint32_t b, uint32_t c) {
  uint32_t r;
  asm("fma.rn.bf16x2 %0, %1, %2, %3;" : "=r"(r) : "r"(a), "r"(b), "r"(c));
  return r;
}
__device__ __forceinline__ float ex2(float x) {
  float r;
  asm("ex2.approx.ftz.f32 %0, %1;" : "=f"(r) : "f"(x));
  return r;
}
__device__ __forceinline__ float bf_lo(uint32_t v) { return __uint_as_float(v << 16); }
__device__ __forceinline__ float bf_hi(uint32_t v) { return __uint_as_float(v & 0xffff0000u); }
__device__ __forceinline__ void wait_counter(const unsigned* p, unsigned target) {
  asm volatile(
      "{\n.reg .pred p;\n.reg .u32 c, v;\n"
      "mov.u32 c, 0;\n"
      "LOOP:\n"
      "ld.acquire.gpu.global.u32 v, [%0];\n"
      "setp.ge.u32 p, v, %1;\n"
      "@p bra.uni DONE;\n"
      "add.u32 c, c, 1;\n"
      "setp.lt.u32 p, c, 4194304;\n"
      "@p bra.uni LOOP;\n"
      "trap;\n"
      "DONE:\n"
      "fence.proxy.async.global;\n}"
      ::"l"(p), "r"(target) : "memory");
}

constexpr uint32_t DESC_HI_A = (1024 >> 4) | (1u << 30);
constexpr uint32_t DESC_HI_B = (3072 >> 4) | (1u << 30);
constexpr uint32_t DESC_HI_F = (2560 >> 4) | (2u << 30);
constexpr uint32_t DESC_HI_S = (2048 >> 4) | (1u << 30);
constexpr uint32_t LBO_B = (1024 >> 4) << 16;
constexpr uint32_t LBO_F = (512 >> 4) << 16;

struct Cons {
  uint32_t wbase, xbase;
  uint32_t full, empty_rem;
  uint32_t ws, wph, xs;
  int lane, wg;
  __device__ __forceinline__ void wait_full() { mbar_wait(full + ws * 8, wph); }
  __device__ __forceinline__ uint32_t adv() { uint32_t s = ws; if (++ws == NW) { ws = 0; wph ^= 1; } return s; }
  __device__ __forceinline__ void advX() { if (++xs == NX) xs = 0; }
  __device__ __forceinline__ void rel(uint32_t s) { if (lane < 2) mbar_arrive_cluster(empty_rem + s * 8); }
  __device__ __forceinline__ void turn_begin() { asm volatile("bar.sync %0, 256;" ::"r"(1 + wg) : "memory"); }
  __device__ __forceinline__ void turn_end() { asm volatile("bar.arrive %0, 256;" ::"r"(2 - wg) : "memory"); }
};

__device__ __forceinline__ void store_oh_part(int i, const uint32_t (&p)[48], __nv_bfloat16* dst, int nparts) {
  const int g = i >> 1, h = i & 1;
  if (i < nparts)
    *reinterpret_cast<uint4*>(dst + 32 * g + h * 8 * KOH) = make_uint4(p[8 * g + h], p[8 * g + 2 + h], p[8 * g + 4 + h], p[8 * g + 6 + h]);
  if (i == 11 && nparts > 0) {
    asm volatile("fence.proxy.async.global;" ::: "memory");
    asm volatile("bar.arrive 5, 288;" ::: "memory");
  }
}
__device__ __forceinline__ float rcp(float x) {
  float r;
  asm("rcp.approx.ftz.f32 %0, %1;" : "=f"(r) : "f"(x));
  return r;
}
__device__ __forceinline__ uint32_t silu_bf16x2(uint32_t d) {
  const float d0 = bf_lo(d), d1 = bf_hi(d);
  return pack_bf16(d0 * rcp(1.0f + ex2(-1.4426950408889634f * d0)), d1 * rcp(1.0f + ex2(-1.4426950408889634f * d1)));
}

template <int NREG, bool FIRST, bool TB, bool TE, bool ZERO = FIRST, bool ADVX = true>
__device__ __forceinline__ void gemm_step(Cons& c, float (&acc)[NREG], uint32_t& prev) {
  if (!FIRST) c.wait_full();
  const uint32_t a = c.xbase + c.xs * (XSLOT >> 4);
  const uint32_t b = c.wbase + c.ws * (WSLOT >> 4);
  if (TB) c.turn_begin();
  wgmma_fence();
#pragma unroll
  for (int kk = 0; kk < 4; kk++) {
    if constexpr (NREG == 96)
      wgmma_ss_n192_t1(acc, mk_desc(a + kk * 2, DESC_HI_A), mk_desc((b | LBO_B) + kk * (6144 >> 4), DESC_HI_B), !(ZERO && kk == 0));
    else if constexpr (NREG == 64)
      wgmma_ss_n128_t1(acc, mk_desc(a + kk * 2, DESC_HI_A), mk_desc((b | LBO_B) + kk * (4096 >> 4), DESC_HI_S), !(ZERO && kk == 0));
    else
      wgmma_ss_n160_t1(acc, mk_desc(a + kk * 2, DESC_HI_A), mk_desc((b | LBO_F) + kk * (5120 >> 4), DESC_HI_F), !(ZERO && kk == 0));
  }
  wgmma_commit();
  if (TE) c.turn_end();
  if (!FIRST) {
    wgmma_wait<1>();
    c.rel(prev);
  }
  prev = c.adv();
  if (ADVX) c.advX();
}
struct NoPack { __device__ __forceinline__ void operator()(int) const {} };
template <int NREG, int SIDE, bool TURN, int NEXT, bool DRAIN = true, class PACK = NoPack>
__device__ __forceinline__ uint32_t gemm(Cons& c, float (&acc)[NREG], int nsteps, uint32_t (&p)[48], __nv_bfloat16* dst, int nparts,
                                         PACK pack = PACK()) {
  constexpr int NPEEL = SIDE == 1 ? 10 : SIDE == 3 ? 2 : 1;
  uint32_t prev = 0;
  pin(acc);
#pragma unroll
  for (int ks = 0; ks < NPEEL; ks++) {
    constexpr bool PAIR = SIDE == 1 || SIDE == 3;
    if (ks == 0) gemm_step<NREG, true, TURN, TURN && !PAIR>(c, acc, prev);
    else if (ks == 1) gemm_step<NREG, false, TURN && !PAIR, TURN>(c, acc, prev);
    else gemm_step<NREG, false, TURN, TURN>(c, acc, prev);
    if (SIDE == 3 && ks == 1) {
#pragma unroll
      for (int i = 0; i < 12; i++) pack(i);
      pin(p);
    }
    if (SIDE == 1) {
      if (ks >= 1 && ks < 5) {
        pack(2 * ks - 2); store_oh_part(2 * ks - 2, p, dst, nparts);
        pack(2 * ks - 1); store_oh_part(2 * ks - 1, p, dst, nparts);
      } else if (ks >= 5 && ks < 9) {
        pack(ks + 3); store_oh_part(ks + 3, p, dst, nparts);
      }
    }
  }
  int ks = NPEEL;
  if (SIDE == 2) {
#pragma unroll 1
    for (int g = 0; g < 8; g++) {
      gemm_step<NREG, false, TURN, TURN>(c, acc, prev);
      p[40] = silu_bf16x2(p[0]);
      p[41] = silu_bf16x2(p[1]);
      asm volatile("" : "+r"(p[40]), "+r"(p[41])::"memory");
      gemm_step<NREG, false, TURN, TURN>(c, acc, prev);
      p[42] = silu_bf16x2(p[2]);
      p[43] = silu_bf16x2(p[3]);
      asm volatile("" : "+r"(p[42]), "+r"(p[43])::"memory");
      gemm_step<NREG, false, TURN, TURN>(c, acc, prev);
      p[44] = silu_bf16x2(p[4]);
      asm volatile("" : "+r"(p[44])::"memory");
      gemm_step<NREG, false, TURN, TURN>(c, acc, prev);
#pragma unroll
      for (int i = 0; i < 40; i++) p[i] = p[i + 5];
    }
    ks += 32;
  }
  if (SIDE == 3) {
#pragma unroll 1
    for (int g = 0; g < 6; g++) {
      store_oh_part(0, p, dst, 12);
      gemm_step<NREG, false, TURN, TURN>(c, acc, prev);
      gemm_step<NREG, false, TURN, TURN>(c, acc, prev);
      store_oh_part(1, p, dst, 12);
      gemm_step<NREG, false, TURN, TURN>(c, acc, prev);
      dst += 32;
#pragma unroll
      for (int i = 0; i < 40; i++) p[i] = p[i + 8];
    }
    ks += 18;
    asm volatile("fence.proxy.async.global;" ::: "memory");
    asm volatile("bar.arrive 5, 288;" ::: "memory");
  }
#pragma unroll 1
  for (; ks < nsteps; ks++) gemm_step<NREG, false, TURN, TURN>(c, acc, prev);
  if (DRAIN) {
    if (NEXT) c.wait_full();
    wgmma_wait<0>();
    pin(acc);
    c.rel(prev);
  }
  return prev;
}

__device__ __forceinline__ void issue_qk(Cons& c, float (&s)[32], uint32_t (&qf)[48], uint32_t slot) {
  uint32_t b = c.wbase + slot * (WSLOT >> 4);
#pragma unroll
  for (int kk = 0; kk < 12; kk++)
    wgmma_rs_n64_t0(s, qf[4 * kk], qf[4 * kk + 1], qf[4 * kk + 2], qf[4 * kk + 3],
                    mk_desc(b + (kk >> 2) * (1024 >> 4) + (kk & 3) * 2, DESC_HI_B), kk > 0);
}
__device__ __forceinline__ void issue_pv(Cons& c, float (&acc)[96], uint32_t (&pf)[16], uint32_t slot, int accum) {
  uint32_t b = (c.wbase + slot * (WSLOT >> 4)) | LBO_B;
#pragma unroll
  for (int kk = 0; kk < 4; kk++)
    wgmma_rs_n192_t1(acc, pf[4 * kk], pf[4 * kk + 1], pf[4 * kk + 2], pf[4 * kk + 3],
                     mk_desc(b + kk * (6144 >> 4), DESC_HI_B), (kk > 0) | accum);
}

constexpr float SM_SCALE = 0.07216878364870322f * 1.4426950408889634f;

constexpr float EXP_LIMIT = 1099511627776.f;

__device__ __forceinline__ void exp_pack(const float (&s)[32], uint32_t (&pf)[16], float c0, float c1, float& t0, float& t1) {
  float u0 = 0.f, u1 = 0.f, w0 = 0.f, w1 = 0.f;
#pragma unroll
  for (int j = 0; j < 8; j++) {
    const float e0 = ex2(fmaf(s[4 * j], SM_SCALE, c0)), e1 = ex2(fmaf(s[4 * j + 1], SM_SCALE, c0));
    const float e2 = ex2(fmaf(s[4 * j + 2], SM_SCALE, c1)), e3 = ex2(fmaf(s[4 * j + 3], SM_SCALE, c1));
    u0 += e0; w0 += e1; u1 += e2; w1 += e3;
    pf[2 * j] = pack_bf16(e0, e1);
    pf[2 * j + 1] = pack_bf16(e2, e3);
  }
  t0 = u0 + w0;
  t1 = u1 + w1;
}
__device__ __forceinline__ void block_max(const float (&s)[32], float& x0, float& x1) {
  float y0 = fmaxf(s[4], s[5]), y1 = fmaxf(s[6], s[7]);
  x0 = fmaxf(s[0], s[1]);
  x1 = fmaxf(s[2], s[3]);
#pragma unroll
  for (int j = 2; j < 8; j += 2) {
    x0 = fmaxf(x0, fmaxf(s[4 * j], s[4 * j + 1]));
    x1 = fmaxf(x1, fmaxf(s[4 * j + 2], s[4 * j + 3]));
    y0 = fmaxf(y0, fmaxf(s[4 * j + 4], s[4 * j + 5]));
    y1 = fmaxf(y1, fmaxf(s[4 * j + 6], s[4 * j + 7]));
  }
  x0 = fmaxf(x0, y0);
  x1 = fmaxf(x1, y1);
  x0 = fmaxf(x0, __shfl_xor_sync(~0u, x0, 1));
  x1 = fmaxf(x1, __shfl_xor_sync(~0u, x1, 1));
  x0 = fmaxf(x0, __shfl_xor_sync(~0u, x0, 2));
  x1 = fmaxf(x1, __shfl_xor_sync(~0u, x1, 2));
  x0 *= -SM_SCALE;
  x1 *= -SM_SCALE;
}

__device__ __forceinline__ void exp_sum(const float (&s)[32], float (&e)[32], float c0, float c1, float& t0, float& t1) {
  float u0 = 0.f, u1 = 0.f, w0 = 0.f, w1 = 0.f;
#pragma unroll
  for (int j = 0; j < 8; j++) {
    e[4 * j] = ex2(fmaf(s[4 * j], SM_SCALE, c0));
    e[4 * j + 1] = ex2(fmaf(s[4 * j + 1], SM_SCALE, c0));
    e[4 * j + 2] = ex2(fmaf(s[4 * j + 2], SM_SCALE, c1));
    e[4 * j + 3] = ex2(fmaf(s[4 * j + 3], SM_SCALE, c1));
    u0 += e[4 * j]; w0 += e[4 * j + 1]; u1 += e[4 * j + 2]; w1 += e[4 * j + 3];
  }
  t0 = u0 + w0;
  t1 = u1 + w1;
}
__device__ __forceinline__ void softmax_rescale(const float (&s)[32], float (&acc)[96], float& c0, float& c1, float& l0, float& l1) {
  float n0, n1;
  block_max(s, n0, n1);
  n0 = fminf(n0, c0);
  n1 = fminf(n1, c1);
  const float a0 = ex2(n0 - c0), a1 = ex2(n1 - c1);
  c0 = n0; c1 = n1;
  l0 *= a0; l1 *= a1;
#pragma unroll
  for (int i = 0; i < 24; i++) {
    acc[4 * i] *= a0; acc[4 * i + 1] *= a0;
    acc[4 * i + 2] *= a1; acc[4 * i + 3] *= a1;
  }
}
__device__ __forceinline__ void row_recip(float l0, float l1, float& r0, float& r1) {
  l0 += __shfl_xor_sync(~0u, l0, 1);
  l1 += __shfl_xor_sync(~0u, l1, 1);
  l0 += __shfl_xor_sync(~0u, l0, 2);
  l1 += __shfl_xor_sync(~0u, l1, 2);
  r0 = rcp(l0);
  r1 = rcp(l1);
}

__global__ void __cluster_dims__(2, 1, 1) __launch_bounds__(384, 1)
fused_kernel(const __grid_constant__ Params P, const __nv_bfloat16* __restrict__ x) {
  extern __shared__ uint8_t smem_raw[];
  const uint32_t s0 = smem_u32(smem_raw);
  const uint32_t wring = (s0 + 256 + 1023) & ~1023u;
  const uint32_t xring = wring + NW * WSLOT;
  const uint32_t full = s0, empty = s0 + 64, xpre = s0 + 128;
  const int tid = threadIdx.x;
  const int warp = __shfl_sync(~0u, tid >> 5, 0);
  const int lane = tid & 31;
  const int rank = blockIdx.x & 1;
  const int cl = blockIdx.x >> 1;
  const bool spare = cl >= 64;
  const int slot = cl & 7;
  const int qt = (cl >> 3) * 2 + rank;
  unsigned* cnt = g_cnt + qt * 32;
  const uint32_t rolebar = s0 + 136, splitbar = s0 + 144, fixbar = s0 + 152, role_s = s0 + 192, split_s = s0 + 196;
  int qf, nc, hi;
  uint32_t parity;
  auto get_role = [&]() {
    mbar_wait(rolebar, 0);
    uint32_t t;
    asm volatile("ld.shared.u32 %0, [%1];" : "=r"(t) : "r"(role_s) : "memory");
    t = __shfl_sync(~0u, t, 0);
    parity = t >> 6;
    t &= 63;
    hi = t < 32;
    const int u = hi ? t : 63 - t;
    qf = (u >> 2) * 2 + rank;
    nc = u & 3;
  };
  auto get_split = [&]() {
    mbar_wait(splitbar, 0);
    uint32_t l;
    asm volatile("ld.shared.u32 %0, [%1];" : "=r"(l) : "r"(split_s) : "memory");
    return (int)__shfl_sync(~0u, l, 0);
  };

  uint2 xv[2][5];
  const int lnrow = qt * 128 + slot * 16 + warp * 2;
  if (warp < 8 && !spare) {
#pragma unroll
    for (int r = 0; r < 2; r++)
#pragma unroll
      for (int i = 0; i < 5; i++)
        xv[r][i] = __ldg(reinterpret_cast<const uint2*>(x + (size_t)(lnrow + r) * DM + i * 128 + lane * 4));
  }
  if (warp == 8 && elect_one()) {
    for (int i = 0; i < NW; i++) { mbar_init(full + i * 8, 1); mbar_init(empty + i * 8, 16); }
    mbar_init(xpre, 1);
    mbar_init(rolebar, 1);
    mbar_init(splitbar, 1);
    mbar_init(fixbar, 1);
    mbar_init(fixbar + 8, 1);
    asm volatile("mbarrier.arrive.expect_tx.shared::cta.b64 _, [%0], 4;" ::"r"(rolebar) : "memory");
    asm volatile("mbarrier.arrive.expect_tx.shared::cta.b64 _, [%0], 4;" ::"r"(splitbar) : "memory");
    asm volatile("fence.mbarrier_init.release.cluster;" ::: "memory");
  }
  __syncwarp();
  asm volatile("barrier.cluster.arrive.relaxed.aligned;" ::: "memory");
  if (warp == 8 && !spare) asm volatile(ELECT "prefetch.tensormap [%0];\n}" ::"l"(&P.xn) : "memory");
  if (warp < 8 && !spare) {
#pragma unroll
    for (int r = 0; r < 2; r++) {
      float v[20];
#pragma unroll
      for (int i = 0; i < 5; i++) {
        v[4 * i] = bf_lo(xv[r][i].x); v[4 * i + 1] = bf_hi(xv[r][i].x);
        v[4 * i + 2] = bf_lo(xv[r][i].y); v[4 * i + 3] = bf_hi(xv[r][i].y);
      }
      float sum = 0.f;
#pragma unroll
      for (int i = 0; i < 20; i++) sum += v[i];
#pragma unroll
      for (int o = 16; o > 0; o >>= 1) sum += __shfl_xor_sync(~0u, sum, o);
      const float mean = sum * (1.0f / DM);
      float sq = 0.f;
#pragma unroll
      for (int i = 0; i < 20; i++) { v[i] -= mean; sq = fmaf(v[i], v[i], sq); }
#pragma unroll
      for (int o = 16; o > 0; o >>= 1) sq += __shfl_xor_sync(~0u, sq, o);
      const float rstd = rsqrtf(sq * (1.0f / DM) + 1e-5f);
#pragma unroll
      for (int i = 0; i < 5; i++) {
        const uint32_t w0 = pack_bf16(v[4 * i] * rstd, v[4 * i + 1] * rstd), w1 = pack_bf16(v[4 * i + 2] * rstd, v[4 * i + 3] * rstd);
        const uint32_t a = xring + (warp * 2 + r) * (XP * 2) + i * 256 + lane * 8;
        asm volatile("st.shared.v2.u32 [%0], {%1, %2};" ::"r"(a), "r"(w0), "r"(w1) : "memory");
      }
    }
    asm volatile("fence.proxy.async.shared::cta;" ::: "memory");
    __syncwarp();
    if (elect_one()) {
      bulk_store(g_xn + (size_t)lnrow * XP, xring + warp * 2 * (XP * 2), 2 * XP * 2);
      asm volatile("cp.async.bulk.commit_group;" ::: "memory");
      asm volatile("cp.async.bulk.wait_group 0;" ::: "memory");
      asm volatile("red.relaxed.gpu.global.add.u32 [%0], 1;" ::"l"(cnt + 8) : "memory");
      asm volatile("fence.proxy.async.global;" ::: "memory");
    }
    __syncwarp();
    asm volatile("bar.arrive 5, 288;" ::: "memory");
  }
  asm volatile("barrier.cluster.wait.aligned;" ::: "memory");

  if (warp >= 8) {
    asm volatile("setmaxnreg.dec.sync.aligned.u32 24;");
    if (warp == 8) {
      uint32_t s = 0, ph = 1, xs = 0;
      uint32_t pbar = 0;
      int pcol = 0;
      const CUtensorMap* xmap = &P.xn;
      int xrow = qt * 128;
      const uint64_t polS = policy_evict_first(), polN = policy_evict_normal();
      uint64_t polX = polN;
      auto acquire = [&]() {
        mbar_wait(empty + s * 8, ph);
        if (pbar) {
          w_tma2d(xring + xs * XSLOT, xmap, pcol, xrow, pbar, polX);
          if (++xs == NX) xs = 0;
          pbar = 0;
        }
      };
      auto advance = [&]() {
        if (++s == NW) { s = 0; ph ^= 1; }
      };
      auto load4 = [&](const CUtensorMap* m, int c2, int c3, int xcol, uint32_t wbytes, uint64_t pol) {
        acquire();
        {
          w_expect_tx(full + s * 8, xcol >= 0 ? wbytes + XSLOT : wbytes);
          w_tma4d_mc(wring + rank * (wbytes >> 1) + s * WSLOT, m, c2, c3 + rank * 4, full + s * 8, pol);
        }
        if (xcol >= 0) { pbar = full + s * 8; pcol = xcol; }
        advance();
      };
      if (spare) {
#pragma unroll 1
        for (int p = 0; p < 8; p++) {
          acquire();
          xrow = (p * 2 + rank) * 128;
          wait_counter(g_cnt + (p * 2 + rank) * 32, ITEM_TARGET);
#pragma unroll 1
          for (int ks = 0; ks < 10; ks++) load4(&P.wg2, 20 + slot * 2, ks * 8, ks * 64, 16384, polN);
#pragma unroll 1
          for (int ks = 0; ks < 10; ks++) {
            const int k = ks < 5 ? ks + 5 : ks - 5;
            load4(&P.wu2, 20 + slot * 2, k * 8, ks < 5 ? -1 : k * 64, 16384, polN);
          }
        }
        acquire();
      } else {
#pragma unroll 1
      for (int ks = 0; ks < NW; ks++) {
        w_expect_tx(full + ks * 8, (ks & 1) ? 20480 : 20480 + XSLOT);
        if (ks < NEARLY)
          w_tma4d_mc(wring + rank * 10240 + ks * WSLOT, (ks & 1) ? &P.wu : &P.wg, slot * 5, (ks >> 1) * 8 + rank * 4, full + ks * 8, polS);
      }
      wait_counter(cnt + 8, ITEM_TARGET);
#pragma unroll 1
      for (int ks = 0; ks < NW; ks++) {
        if (ks >= NEARLY)
          w_tma4d_mc(wring + rank * 10240 + ks * WSLOT, (ks & 1) ? &P.wu : &P.wg, slot * 5, (ks >> 1) * 8 + rank * 4, full + ks * 8, polS);
        if (!(ks & 1)) w_tma2d(xring + (ks >> 1) * XSLOT, &P.xn, (ks >> 1) * 64, xrow, full + ks * 8, polN);
      }
      wait_counter(cnt + 0, ITEM_TARGET);
      ph = 0;
      xs = NXE;
#pragma unroll 1
      for (int k = NXE; k < 10; k++) {
        load4(&P.wg, slot * 5, k * 8, k * 64, 20480, polS);
        load4(&P.wu, slot * 5, k * 8, -1, 20480, polS);
      }
#pragma unroll 1
      for (int it = 0; it < 4; it++) {
        const int h = it * 8 + slot;
#pragma unroll 1
        for (int ks = 0; ks < 10; ks++) {
          const int k = (it & 1) ? ks : (ks < 5 ? ks + 5 : ks - 5);
          load4(&P.wq, h * 3, k * 8, ks < 5 ? -1 : k * 64, WSLOT, polS);
        }
        const int g0 = (h * SKV + (SKV - WIN)) / 8;
        load4(&P.k, 0, g0, -1, WSLOT, polS);
#pragma unroll 1
        for (int j = 0; j < (it < 3 ? 7 : 4); j++) {
          load4(&P.k, 0, g0 + (j + 1) * 8, -1, WSLOT, polS);
          load4(&P.v, 0, g0 + j * 8, -1, WSLOT, polS);
        }
        if (it < 3) load4(&P.v, 0, g0 + 56, -1, WSLOT, polS);
      }
      get_role();
      unsigned* cntf = g_cnt + qf * 32;
      xmap = &P.oh;
      xrow = qf * 128;
      polX = polS;
      pcol = hi ? 96 * 64 : 0;
      wait_counter(cntf + (hi ? 1 : 2), ITEM_TARGET);
      w_expect_tx(xpre, NX * XSLOT);
      {
        const int g0 = ((24 + slot) * SKV + (SKV - WIN)) / 8;
#pragma unroll 1
        for (int j = 4; j < 7; j++) {
          pbar = xpre;
          load4(&P.k, 0, g0 + (j + 1) * 8, -1, WSLOT, polS);
          pcol += 64;
          if (j < 6) pbar = xpre;
          load4(&P.v, 0, g0 + j * 8, -1, WSLOT, polS);
          pcol += 64;
        }
        load4(&P.v, 0, g0 + 56, -1, WSLOT, polS);
      }
      const CUtensorMap* wmap = hi ? &P.wd : &P.wo;
      int kw = rank * 4, kc = hi ? 96 * 64 : 0;
#pragma unroll 1
      for (int n = 0; n < NX; n++) {
        acquire();
        {
          w_expect_tx(full + s * 8, 20480);
          w_tma5d_mc(wring + rank * 10240 + s * WSLOT, wmap, kw, nc * 5, full + s * 8, polS);
        }
        advance();
        kw += 8;
      }
      kc += NX * 64;
      auto fin_first = [&]() {
        acquire();
        {
          w_expect_tx(full + s * 8, 20480 + XSLOT);
          w_tma5d_mc(wring + rank * 10240 + s * WSLOT, wmap, kw, nc * 5, full + s * 8, polS);
        }
        pbar = full + s * 8; pcol = kc;
        advance();
        kw += 8; kc += 64;
      };
      auto fin_steps = [&](int cnt_) {
#pragma unroll 1
        for (int n = 0; n < cnt_; n++) {
          mbar_wait(empty + s * 8, ph);
          const uint32_t fb = full + s * 8;
          {
            w_tma2d(xring + xs * XSLOT, &P.oh, pcol, xrow, pbar, polS);
            w_expect_tx(fb, 20480 + XSLOT);
            w_tma5d_mc(wring + rank * 10240 + s * WSLOT, wmap, kw, nc * 5, fb, polS);
          }
          if (++xs == NX) xs = 0;
          pbar = fb; pcol = kc;
          advance();
          kw += 8; kc += 64;
        }
      };
      fin_first();
      fin_steps(15);
      if (hi) wait_counter(cntf + 7, 16);
      fin_steps(3);
      if (hi) { kw = 48 * 8 + rank * 4; kc = 48 * 64; wmap = &P.wo; }
      fin_steps(1);
      wait_counter(cntf + 3 + hi, ITEM_TARGET);
      fin_steps(23);
      const int L = get_split();
      kc = hi ? 72 + L - 48 : 72;
      kw = kc * 8 + rank * 4;
      kc *= 64;
      fin_steps(1);
      wait_counter(cntf + 5, ITEM_TARGET);
      asm volatile("bar.arrive 8, 64;" ::: "memory");
      fin_steps(hi ? 120 - L - 49 - 2 : L - 49);
      if (hi) {
#pragma unroll 1
        for (int w = 0; w < 2; w++) {
          acquire();
          {
            w_expect_tx(full + s * 8, 20480);
#pragma unroll
            for (int q = 0; q < 4; q++)
              w_tma3d(wring + s * WSLOT + q * 5120, &P.x, 0, qf * 128 + w * 64 + q * 16, nc * 5, full + s * 8);
          }
          advance();
        }
        fin_first();
        fin_first();
      }
      acquire();
      if (hi) {
#pragma unroll 1
        for (int w = 0; w < 2; w++) {
          unsigned* flag = g_flag_part + ((qf * 4 + nc) * 2 + w) * 8;
          acquire();
          w_expect_tx(full + s * 8, 20480);
          wait_counter(flag, 4);
          w_bulk_load(wring + s * WSLOT, g_part + ((qf * 4 + nc) * 2 + w) * 1280, 20480, full + s * 8);
          asm volatile(ELECT "st.relaxed.gpu.global.u32 [%0], %1;\n}" ::"l"(flag), "r"(0u) : "memory");
          advance();
        }
      }
      }
    } else if (warp == 11) {
      if (!spare) {
        const uint32_t zeros = xring + NX * XSLOT + 512;
#pragma unroll
        for (int i = 0; i < 5; i++) asm volatile("st.shared.u32 [%0], %1;" ::"r"(zeros + i * 128 + lane * 4), "r"(0u) : "memory");
        asm volatile("fence.proxy.async.shared::cta;" ::: "memory");
        asm volatile("bar.sync 8, 64;" ::: "memory");
        get_role();
        wait_counter(g_cnt + qf * 32 + 7, 16);
        if (lane < 16) bulk_store(g_xn + (size_t)(qf * 128 + (hi * 4 + nc) * 16 + lane) * XP, zeros, NXE * 128);
        asm volatile("cp.async.bulk.commit_group;" ::: "memory");
        asm volatile("cp.async.bulk.wait_group.read 0;" ::: "memory");
        __syncwarp();
        if (lane == 0) {
          unsigned* cntf = g_cnt + qf * 32;
          fence_gpu();
          if (atomicAdd(cntf + 6, 1) == 7) {
            fence_gpu();
#pragma unroll
            for (int i = 0; i < 9; i++) cntf[i] = 0;
          }
        }
        __syncwarp();
      }
    } else if (warp == 10) {
      if (!spare && rank == 0) {
        uint32_t c0, g0, c1, g1, t = 0, ep = 0, v;
        asm volatile("mov.u32 %0, %%clock;" : "=r"(c0));
        asm volatile("mov.u32 %0, %%globaltimer_lo;" : "=r"(g0));
        asm volatile("bar.sync 7, 64;" ::: "memory");
        asm volatile("mov.u32 %0, %%clock;" : "=r"(c1));
        asm volatile("mov.u32 %0, %%globaltimer_lo;" : "=r"(g1));
        if (lane == 0) {
          asm volatile("ld.relaxed.gpu.global.u32 %0, [%1];" : "=r"(ep) : "l"(&g_epoch) : "memory");
          uint32_t one = 1;
          asm volatile("{\n.reg .pred p;\nsetp.gt.u32 p, %1, 1;\n@p trap;\n}" : "+r"(one) : "r"(ep) : "memory");
          t = atomicAdd(&g_ticket, one);
          if (t == 63) {
            atomicExch(&g_ticket, 0);
            atomicExch(&g_epoch, ep ^ 1);
          }
        }
        t = __shfl_sync(~0u, t, 0);
        ep = __shfl_sync(~0u, ep, 0);
        uint32_t ra;
        asm volatile("mapa.shared::cluster.u32 %0, %1, %2;" : "=r"(ra) : "r"(s0), "r"(lane & 1));
        if (lane < 2)
          asm volatile("st.async.weak.shared::cluster.mbarrier::complete_tx::bytes.u32 [%0], %1, [%2];"
                       ::"r"(ra + 192), "r"(t | ((ep ^ 1) << 6)), "r"(ra + 136) : "memory");
        const uint32_t fin = (g1 + (uint32_t)((float)(g1 - g0) * (SCHED_R / (float)(c1 - c0)))) | 1u;
        unsigned* sc = g_sched + (t < 32 ? t : 63 - t) * 16;
        if (t < 32 && lane == 0) asm volatile("st.relaxed.gpu.global.u32 [%0], %1;" ::"l"(sc), "r"(fin) : "memory");
        unsigned* src = t < 32 ? sc + 8 : sc;
        for (int i = 0;; i++) {
          asm volatile("ld.relaxed.gpu.global.u32 %0, [%1];" : "=r"(v) : "l"(src) : "memory");
          if (v != 0) break;
          if (i > (1 << 22)) __trap();
          __nanosleep(100);
        }
        __syncwarp();
        if (lane == 0) asm volatile("st.relaxed.gpu.global.u32 [%0], %1;" ::"l"(src), "r"(0u) : "memory");
        if (t >= 32) {
          const float d = (float)(int)(fin - v) + SCHED_P;
          v = min(61, max(50, 60 - __float2int_rn(d * (1.0f / 830.f))));
          if (lane == 0) asm volatile("st.relaxed.gpu.global.u32 [%0], %1;" ::"l"(sc + 8), "r"(v) : "memory");
        }
        if (lane < 2)
          asm volatile("st.async.weak.shared::cluster.mbarrier::complete_tx::bytes.u32 [%0], %1, [%2];"
                       ::"r"(ra + 196), "r"(v), "r"(ra + 144) : "memory");
        __syncwarp();
      }
    } else if (warp == 9) {
#pragma unroll 1
      for (int it = spare ? 0 : -1; it < (spare ? 8 : 5); it++) {
        asm volatile("bar.sync 5, 288;" ::: "memory");
        if (it == 3 && !spare && rank == 0) asm volatile("bar.arrive 7, 64;" ::: "memory");
        if (lane == 0) {
          fence_gpu();
          unsigned* dst = spare ? g_cnt + (it * 2 + rank) * 32 + 7 : cnt + 1 + it;
          asm volatile("red.relaxed.gpu.global.add.u32 [%0], %1;" ::"l"(dst), "r"(8u) : "memory");
        }
        __syncwarp();
      }
      hi = 0;
      if (!spare) get_role();
      if (hi && elect_one()) {
#pragma unroll 1
        for (int q = 0; q < 8; q++)
          asm volatile("cp.async.bulk.prefetch.tensor.3d.L2.global [%0, {%1, %2, %3}];"
                       ::"l"(&P.x), "r"(0), "r"(qf * 128 + q * 16), "r"(nc * 5) : "memory");
        asm volatile("prefetch.tensormap [%0];" ::"l"(&P.out) : "memory");
      }
      __syncwarp();
    }
  } else {
    asm volatile("setmaxnreg.inc.sync.aligned.u32 240;");
    Cons c;
    c.lane = lane;
    c.wg = warp >> 2;
    c.wbase = (wring & 0x3FFFF) >> 4;
    c.xbase = (((xring + c.wg * 8192) & 0x3FFFF) >> 4) | (1u << 16);
    c.full = full;
    asm volatile("mapa.shared::cluster.u32 %0, %1, %2;" : "=r"(c.empty_rem) : "r"(empty), "r"(lane & 1));
    c.ws = c.wph = c.xs = 0;
    if (c.wg == 1) asm volatile("bar.arrive 1, 256;" ::: "memory");
    uint32_t qf_[48];
    if (spare) {
      float acc[64];
      __nv_bfloat16* pend = g_oh + (size_t)(rank * 128 + warp * 16 + (lane >> 2)) * KOH + (lane & 3) * 8 + NH * DH + 1280 + slot * 128;
#pragma unroll 1
      for (int p = 0; p < 8; p++) {
        c.wait_full();
        gemm<64, 1, true, true>(c, acc, 10, qf_, pend - 256 * KOH, p > 0 ? 8 : 0);
#pragma unroll
        for (int i = 0; i < 32; i++) qf_[i] = pack_bf16(acc[2 * i], acc[2 * i + 1]);
        gemm<64, 0, true, false>(c, acc, 10, qf_, nullptr, 0);
#pragma unroll
        for (int i = 0; i < 32; i++) qf_[i] = mul_bf16x2(qf_[i], pack_bf16(acc[2 * i], acc[2 * i + 1]));
        pend += 256 * KOH;
      }
#pragma unroll
      for (int i = 0; i < 12; i++) store_oh_part(i, qf_, pend - 256 * KOH, 8);
    } else {
    const int row = qt * 128 + warp * 16 + (lane >> 2);
    __nv_bfloat16* ohrow = g_oh + (size_t)row * KOH + (lane & 3) * 8;
    __nv_bfloat16* pend = ohrow + NH * DH + slot * 160;
    float o[96], r0 = 1.f, r1 = 1.f;
    auto pack_o = [&](int i) {
      const int g = i >> 1, h = i & 1;
      float r = h ? r1 : r0;
      asm volatile("" : "+f"(r)::"memory");
#pragma unroll
      for (int q = 0; q < 4; q++) qf_[8 * g + 2 * q + h] = pack_bf16(o[16 * g + 4 * q + 2 * h] * r, o[16 * g + 4 * q + 2 * h + 1] * r);
    };
    {
      float acc[80];
      uint32_t prev = 0, fixph = 0;
      auto validate = [&](int ks) {
        c.wait_full();
        const uint32_t a = xring + ks * XSLOT + c.wg * 8192 + (tid & 127) * 32 + ((lane >> 2) << 2);
        uint32_t v0, v1, bad;
        asm volatile("ld.shared.u32 %0, [%1];" : "=r"(v0) : "r"(a) : "memory");
        asm volatile("ld.shared.u32 %0, [%1];" : "=r"(v1) : "r"(a + 4096) : "memory");
        asm volatile("{\n.reg .pred p, q;\nsetp.ne.u32 p, %1, 0;\nbarrier.red.or.pred q, %2, 128, p;\nselp.u32 %0, 1, 0, q;\n}"
                     : "=r"(bad) : "r"((uint32_t)(v0 == 0 || v1 == 0)), "r"(3 + c.wg) : "memory");
        if (__builtin_expect(__shfl_sync(~0u, bad, 0), 0)) {
          if ((warp & 3) == 0) {
            wait_counter(cnt + 0, ITEM_TARGET);
            w_expect_tx(fixbar + c.wg * 8, XSLOT);
            w_tma2d(xring + ks * XSLOT, &P.xn, ks * 64, qt * 128, fixbar + c.wg * 8, policy_evict_normal());
          }
          mbar_wait(fixbar + c.wg * 8, fixph);
          fixph ^= 1;
        }
      };
      float accu[80];
      validate(0);
      pin(acc); pin(accu);
      gemm_step<80, true, true, true, true, false>(c, acc, prev);
      gemm_step<80, false, true, true, true, true>(c, accu, prev);
#pragma unroll 1
      for (int ks = 1; ks < 9; ks++) {
        if (ks < NXE) validate(ks);
        gemm_step<80, false, true, true, false, false>(c, acc, prev);
        gemm_step<80, false, true, true, false, true>(c, accu, prev);
      }
      gemm_step<80, false, true, false, false, false>(c, acc, prev);
      gemm_step<80, false, false, true, false, true>(c, accu, prev);
      c.wait_full();
      wgmma_wait<0>();
      pin(acc); pin(accu);
      c.rel(prev);
#pragma unroll
      for (int i = 0; i < 80; i++) o[i] = acc[i] * accu[i];
#pragma unroll
      for (int i = 80; i < 96; i++) o[i] = 0.f;
    }
    {
#pragma unroll 1
      for (int it = 0; it < 4; it++) {
        {
          float accq[96];
          gemm<96, 1, true, 1, true>(c, accq, 10, qf_, pend, it == 0 ? 10 : 12, pack_o);
#pragma unroll
          for (int i = 0; i < 48; i++) qf_[i] = pack_bf16(accq[2 * i], accq[2 * i + 1]);
        }
        float (&acc)[96] = o;
#pragma unroll
        for (int i = 0; i < 96; i++) asm volatile("" : "=f"(o[i])::"memory");
        float s[32];
        uint32_t pf[16];
        float c0, c1, l0, l1;
        uint32_t sk, sv;
        {
          sk = c.adv();
          c.turn_begin();
          pin(qf_);
          wgmma_fence();
          issue_qk(c, s, qf_, sk);
          wgmma_commit();
          c.turn_end();
          const uint32_t sk0 = sk;
          c.wait_full();
          sk = c.adv();
          c.wait_full();
          sv = c.adv();
          wgmma_wait<0>();
          pin(s);
          c.rel(sk0);
          c0 = -SM_SCALE * __shfl_sync(~0u, s[0], lane & ~3);
          c1 = -SM_SCALE * __shfl_sync(~0u, s[2], lane & ~3);
          exp_pack(s, pf, c0, c1, l0, l1);
          if (__builtin_expect(__any_sync(~0u, !(l0 <= EXP_LIMIT && l1 <= EXP_LIMIT)), 0)) {
            block_max(s, c0, c1);
            exp_pack(s, pf, c0, c1, l0, l1);
          }
        }
#pragma unroll 1
        for (int j = 0; j < 6; j++) {
          c.turn_begin();
          pin(s); pin(pf); pin(acc);
          wgmma_fence();
          issue_qk(c, s, qf_, sk);
          issue_pv(c, acc, pf, sv, j > 0);
          wgmma_commit();
          c.turn_end();
          const uint32_t sk0 = sk, sv0 = sv;
          c.wait_full();
          sk = c.adv();
          c.wait_full();
          sv = c.adv();
          wgmma_wait<0>();
          pin(s); pin(acc); pin(pf);
          c.rel(sk0);
          c.rel(sv0);
          float t0, t1;
          exp_pack(s, pf, c0, c1, t0, t1);
          if (__builtin_expect(__any_sync(~0u, !(t0 <= EXP_LIMIT && t1 <= EXP_LIMIT)), 0)) {
            softmax_rescale(s, acc, c0, c1, l0, l1);
            exp_pack(s, pf, c0, c1, t0, t1);
          }
          l0 += t0;
          l1 += t1;
        }
        uint32_t pl[16];
        {
          c.turn_begin();
          pin(s); pin(pf); pin(acc);
          wgmma_fence();
          issue_qk(c, s, qf_, sk);
          wgmma_commit();
          issue_pv(c, acc, pf, sv, 1);
          wgmma_commit();
          c.turn_end();
          const uint32_t sv0 = sv;
          c.wait_full();
          sv = c.adv();
          wgmma_wait<1>();
          pin(s);
          c.rel(sk);
          float e[32], t0, t1;
          exp_sum(s, e, c0, c1, t0, t1);
          pin(e);
          wgmma_wait<0>();
          pin(acc); pin(pf);
          c.rel(sv0);
          if (__builtin_expect(__any_sync(~0u, !(t0 <= EXP_LIMIT && t1 <= EXP_LIMIT)), 0)) {
            softmax_rescale(s, acc, c0, c1, l0, l1);
            exp_sum(s, e, c0, c1, t0, t1);
          }
          l0 += t0;
          l1 += t1;
#pragma unroll
          for (int i = 0; i < 16; i++) pl[i] = pack_bf16(e[2 * i], e[2 * i + 1]);
        }
        {
          c.turn_begin();
          pin(pl); pin(acc);
          wgmma_fence();
          issue_pv(c, acc, pl, sv, 1);
          wgmma_commit();
          c.turn_end();
          row_recip(l0, l1, r0, r1);
          asm volatile("" : "+f"(r0), "+f"(r1)::"memory");
          c.wait_full();
          if (it == 3) mbar_wait(xpre, 0);
          wgmma_wait<0>();
          pin(acc); pin(pl);
          c.rel(sv);
          pend = ohrow + (it * 8 + slot) * DH;
        }
      }
    }

    {
      float acc[80];
      uint32_t prev = gemm<80, 3, true, 0, false>(c, acc, 20, qf_, pend, 12, pack_o);
      get_role();
      const int L = get_split();
#pragma unroll 1
      for (int ks = 20; ks < (hi ? 24 : L) - PAIR_LO; ks++) gemm_step<80, false, true, true>(c, acc, prev);
      if (PAIR_LO) {
        c.turn_begin();
#pragma unroll 1
        for (int ks = 0; ks < PAIR_LO; ks++) gemm_step<80, false, false, false>(c, acc, prev);
        c.turn_end();
      }
      wgmma_wait<0>();
      pin(acc);
      c.rel(prev);
#pragma unroll
      for (int i = 0; i < 40; i++) qf_[i] = pack_bf16(acc[2 * i], acc[2 * i + 1]);
      if (!hi) {
        if (c.wg == 1) c.adv();
        const uint32_t st = wring + c.ws * WSLOT + (warp & 3) * 5120;
#pragma unroll
        for (int i = 0; i < 10; i++)
          asm volatile("st.shared.v4.u32 [%0], {%1, %2, %3, %4};" ::"r"(st + i * 512 + lane * 16), "r"((qf_[4 * i] & ~1u) | parity),
                       "r"(qf_[4 * i + 1]), "r"(qf_[4 * i + 2]), "r"(qf_[4 * i + 3]) : "memory");
        asm volatile("fence.proxy.async.shared::cta;" ::: "memory");
        __syncwarp();
        if (elect_one()) {
          bulk_store(g_part + ((qf * 4 + nc) * 8 + warp) * 320, st, 5120);
          asm volatile("cp.async.bulk.commit_group;" ::: "memory");
          asm volatile("cp.async.bulk.wait_group 0;" ::: "memory");
          asm volatile("red.relaxed.gpu.global.add.u32 [%0], 1;" ::"l"(g_flag_part + ((qf * 4 + nc) * 2 + c.wg) * 8) : "memory");
        }
        __syncwarp();
      } else {
        c.wait_full();
        prev = gemm<80, 2, false, false, false>(c, acc, 96 - L - 2, qf_, nullptr, 0);
        if (c.wg == 1) c.adv();
        c.wait_full();
        const uint32_t xt = wring + c.ws * WSLOT + (warp & 3) * 5120;
        const int r = (lane & 7) + ((lane >> 3) & 1) * 8;
        const uint32_t xa = xt + r * 64 + (((lane >> 4) ^ ((r >> 1) & 3)) << 4);
        c.adv();
        if (c.wg == 0) c.adv();
        gemm_step<80, false, true, false>(c, acc, prev);
        gemm_step<80, false, false, true>(c, acc, prev);
        uint32_t xr[40], pr[40];
#pragma unroll
        for (int i = 0; i < 10; i++)
          asm volatile("ldmatrix.sync.aligned.m8n8.x4.shared.b16 {%0, %1, %2, %3}, [%4];"
                       : "=r"(xr[4 * i]), "=r"(xr[4 * i + 1]), "=r"(xr[4 * i + 2]), "=r"(xr[4 * i + 3])
                       : "r"((xa ^ ((i & 1) * 32)) + (i >> 1) * 1024) : "memory");
        if (c.wg == 1) c.adv();
        wgmma_wait<0>();
        pin(acc);
        uint32_t sp[40];
#pragma unroll
        for (int q = 0; q < 40; q++) sp[q] = pack_bf16(acc[2 * q], acc[2 * q + 1]);
        pin(sp);
        c.wait_full();
        const uint32_t pt = wring + c.ws * WSLOT + (warp & 3) * 5120 + lane * 16;
#pragma unroll
        for (int i = 0; i < 10; i++)
          asm volatile("ld.shared.v4.u32 {%0, %1, %2, %3}, [%4];"
                       : "=r"(pr[4 * i]), "=r"(pr[4 * i + 1]), "=r"(pr[4 * i + 2]), "=r"(pr[4 * i + 3]) : "r"(pt + i * 512) : "memory");
#pragma unroll 1
        for (int n = 0;; n++) {
          uint32_t stale = 0;
#pragma unroll
          for (int i = 0; i < 10; i++) {
            stale |= pr[4 * i] ^ parity;
            asm volatile("stmatrix.sync.aligned.m8n8.x4.shared.b16 [%4], {%0, %1, %2, %3};"
                         ::"r"(fma_bf16x2(add_bf16x2(sp[4 * i], pr[4 * i]), qf_[4 * i], xr[4 * i])),
                           "r"(fma_bf16x2(add_bf16x2(sp[4 * i + 1], pr[4 * i + 1]), qf_[4 * i + 1], xr[4 * i + 1])),
                           "r"(fma_bf16x2(add_bf16x2(sp[4 * i + 2], pr[4 * i + 2]), qf_[4 * i + 2], xr[4 * i + 2])),
                           "r"(fma_bf16x2(add_bf16x2(sp[4 * i + 3], pr[4 * i + 3]), qf_[4 * i + 3], xr[4 * i + 3])),
                           "r"((xa ^ ((i & 1) * 32)) + (i >> 1) * 1024) : "memory");
          }
          if (!__any_sync(~0u, stale & 1)) break;
          if (n > (1 << 22)) __trap();
          const uint4* src = g_part + ((qf * 4 + nc) * 8 + warp) * 320 + lane;
#pragma unroll
          for (int i = 0; i < 10; i++)
            asm volatile("ld.relaxed.gpu.global.v4.u32 {%0, %1, %2, %3}, [%4];"
                         : "=r"(pr[4 * i]), "=r"(pr[4 * i + 1]), "=r"(pr[4 * i + 2]), "=r"(pr[4 * i + 3]) : "l"(src + i * 32) : "memory");
        }
        asm volatile("fence.proxy.async.shared::cta;" ::: "memory");
        __syncwarp();
        if (elect_one()) {
          asm volatile("cp.async.bulk.tensor.3d.global.shared::cta.bulk_group [%0, {%2, %3, %4}], [%1];"
                       ::"l"(&P.out), "r"(xt), "r"(0), "r"(qf * 128 + warp * 16), "r"(nc * 5) : "memory");
          asm volatile("cp.async.bulk.commit_group;" ::: "memory");
          asm volatile("cp.async.bulk.wait_group.read 0;" ::: "memory");
        }
        __syncwarp();
      }
    }
    }
  }
  asm volatile("barrier.cluster.arrive.relaxed.aligned;" ::: "memory");
  asm volatile("barrier.cluster.wait.aligned;" ::: "memory");
}

typedef CUresult (*EncodeFn)(CUtensorMap*, CUtensorMapDataType, cuuint32_t, void*, const cuuint64_t*, const cuuint64_t*,
                             const cuuint32_t*, const cuuint32_t*, CUtensorMapInterleave, CUtensorMapSwizzle,
                             CUtensorMapL2promotion, CUtensorMapFloatOOBfill);

void make_map(EncodeFn enc, CUtensorMap* m, const void* ptr, int rank, const cuuint64_t* dims, const cuuint64_t* strides,
              const cuuint32_t* box, CUtensorMapSwizzle sw) {
  cuuint32_t es[5] = {1, 1, 1, 1, 1};
  enc(m, CU_TENSOR_MAP_DATA_TYPE_BFLOAT16, rank, const_cast<void*>(ptr), dims, strides, box, es,
      CU_TENSOR_MAP_INTERLEAVE_NONE, sw, CU_TENSOR_MAP_L2_PROMOTION_L2_128B, CU_TENSOR_MAP_FLOAT_OOB_FILL_NONE);
}

void map_b(EncodeFn enc, CUtensorMap* m, const void* ptr, uint64_t rows, uint64_t cols, uint32_t cw, uint32_t nchunk) {
  cuuint64_t d[4] = {cw, 8, cols / cw, rows / 8};
  cuuint64_t s[3] = {cols * 2, cw * 2, cols * 2 * 8};
  cuuint32_t b[4] = {cw, 8, nchunk, 4};
  make_map(enc, m, ptr, 4, d, s, b, cw == 64 ? CU_TENSOR_MAP_SWIZZLE_128B : CU_TENSOR_MAP_SWIZZLE_64B);
}
void map_b160(EncodeFn enc, CUtensorMap* m, const void* ptr, uint64_t rows) {
  const uint64_t p = DM * 2;
  cuuint64_t d[5] = {32, 2, rows / 8, DM / 32, 4};
  cuuint64_t s[4] = {p, 8 * p, 64, 2 * p};
  cuuint32_t b[5] = {32, 2, 4, 5, 4};
  make_map(enc, m, ptr, 5, d, s, b, CU_TENSOR_MAP_SWIZZLE_64B);
}
void map_a(EncodeFn enc, CUtensorMap* m, const void* ptr, uint64_t cols, uint32_t boxrows) {
  cuuint64_t d[2] = {cols, SEQ};
  cuuint64_t s[1] = {cols * 2};
  cuuint32_t b[2] = {64, boxrows};
  make_map(enc, m, ptr, 2, d, s, b, CU_TENSOR_MAP_SWIZZLE_128B);
}
void map_xo(EncodeFn enc, CUtensorMap* m, const void* ptr) {
  cuuint64_t d[3] = {32, SEQ, DM / 32};
  cuuint64_t s[2] = {DM * 2, 64};
  cuuint32_t b[3] = {32, 16, 5};
  make_map(enc, m, ptr, 3, d, s, b, CU_TENSOR_MAP_SWIZZLE_64B);
}

}

extern "C" void kernel_launch(void* const* d_in, const int* in_sizes, int n_in, void* d_out, int out_size) {
  void* fn = nullptr;
  cudaDriverEntryPointQueryResult qr;
  cudaGetDriverEntryPoint("cuTensorMapEncodeTiled", &fn, cudaEnableDefault, &qr);
  EncodeFn enc = (EncodeFn)fn;
  void* sp;
  cudaGetSymbolAddress(&sp, g_s);
  void* xn = (char*)sp + offsetof(Scratch, xn);
  void* oh = (char*)sp + offsetof(Scratch, oh);
  Params P;
    map_a(enc, &P.xn, xn, XP, 128);
  map_a(enc, &P.oh, oh, KOH, 128);
  map_b(enc, &P.wq, d_in[3], DM, NH * DH, 64, 3);
  map_b(enc, &P.wg, d_in[6], DM, FF, 32, 5);
  map_b(enc, &P.wu, d_in[7], DM, FF, 32, 5);
  map_b(enc, &P.wg2, d_in[6], DM, FF, 64, 2);
  map_b(enc, &P.wu2, d_in[7], DM, FF, 64, 2);
  map_b(enc, &P.k, d_in[1], (uint64_t)NH * SKV, DH, 64, 3);
  map_b(enc, &P.v, d_in[2], (uint64_t)NH * SKV, DH, 64, 3);
  map_b160(enc, &P.wo, d_in[4], NH * DH);
  map_b160(enc, &P.wd, d_in[8], FF);
  map_xo(enc, &P.x, d_in[0]);
  map_xo(enc, &P.out, d_out);
  cudaFuncSetAttribute(fused_kernel, cudaFuncAttributeMaxDynamicSharedMemorySize, SMEM_BYTES);
  fused_kernel<<<132, 384, SMEM_BYTES>>>(P, (const __nv_bfloat16*)d_in[0]);
}
```
